```python
import torch

def _softmax(x, axis=-1):
    return torch.softmax(x, dim=axis)

def _gelu(x):
    return torch.nn.functional.gelu(x, approximate='tanh')

def _silu(x):
    return torch.nn.functional.silu(x)

def _sigmoid(x):
    return torch.sigmoid(x)

def _layernorm(x, axis=-1, eps=1e-05):
    m = x.mean(dim=axis, keepdim=True)
    v = x.var(dim=axis, keepdim=True, unbiased=False)
    return (x - m) / torch.sqrt(v + eps)

def _scatter_add(tgt, idx, src, axis=0):
    return tgt.clone().index_add_(axis, idx, src)

def _segment_sum(src, seg, n):
    out = torch.zeros((n,) + src.shape[1:], dtype=src.dtype)
    return out.index_add_(0, seg, src)

def _pad(x, pw):
    flat = tuple((v for pair in reversed(pw) for v in pair))
    return torch.nn.functional.pad(x, flat)
kernel_name = 'recurrent_scan__memory_aug_recurrent_mem_tr__mixer_s_mlp__prompt'

def setup_inputs():

    _w = lambda a: (lambda t: t.to(torch.bfloat16) if t.is_floating_point() else t)(torch.as_tensor(a))

    def _A_setup():
        B, S, Dm = (1, 2048, 1024)
        H, Dh = (32, 128)
        M, seg = (8, 32)
        seg = min(seg, S)
        S = S // seg * seg
        return {'x': _w((lambda *s: torch.randn(*s, dtype=torch.bfloat16) * 0.05)(B, S, Dm)), 'mem0': _w((lambda *s: torch.randn(*s, dtype=torch.bfloat16) * 0.2)(B, M, Dm)), 'Wq': _w((lambda *s: torch.randn(*s, dtype=torch.bfloat16) * 1.6)(Dm, H, Dh) * Dm ** (-0.5)), 'Wk': _w((lambda *s: torch.randn(*s, dtype=torch.bfloat16) * 1.6)(Dm, H, Dh) * Dm ** (-0.5)), 'Wv': _w((lambda *s: torch.randn(*s, dtype=torch.bfloat16) * 0.2)(Dm, H, Dh) * Dm ** (-0.5)), 'Wo': _w((lambda *s: torch.randn(*s, dtype=torch.bfloat16) * 0.2)(H, Dh, Dm) * (H * Dh) ** (-0.5)), 'seg_len': seg}
    _A_in = _A_setup()

    def _B_setup():
        B, S, D, F = (1, 2048, 1024, 3584)
        return {'x': _w((lambda *s: torch.randn(*s, dtype=torch.bfloat16) * 0.05)(B, S, D)), 'w1': _w((lambda *s: torch.randn(*s, dtype=torch.bfloat16) * 3.2)(D, D) * D ** (-0.5)), 'w2': _w((lambda *s: torch.randn(*s, dtype=torch.bfloat16) * 3.2)(D, D) * D ** (-0.5)), 'w3': _w((lambda *s: torch.randn(*s, dtype=torch.bfloat16) * 3.2)(D, F) * D ** (-0.5)), 'w4': _w((lambda *s: torch.randn(*s, dtype=torch.bfloat16) * 3.2)(F, D) * F ** (-0.5))}
    _B_in = _B_setup()
    return {'A_x': _A_in['x'], 'A_mem0': _A_in['mem0'], 'A_Wq': _A_in['Wq'], 'A_Wk': _A_in['Wk'], 'A_Wv': _A_in['Wv'], 'A_Wo': _A_in['Wo'], 'A_seg_len': _A_in['seg_len'], 'B_x': _B_in['x'], 'B_w1': _B_in['w1'], 'B_w2': _B_in['w2'], 'B_w3': _B_in['w3'], 'B_w4': _B_in['w4']}

def reference(A_x, A_mem0, A_Wq, A_Wk, A_Wv, A_Wo, A_seg_len, B_x, B_w1, B_w2, B_w3, B_w4):

    def _A_ref(x, mem0, Wq, Wk, Wv, Wo, seg_len):
        B, S, Dm = x.shape
        H, Dh = (Wq.shape[1], Wq.shape[2])
        M = mem0.shape[1]
        scale = Dh ** (-0.5)
        n_seg = S // seg_len
        L = M + seg_len
        idx = torch.arange(L)
        mask = (idx[:, None] < M) | (idx[:, None] >= idx[None, :])
        mem = mem0
        outs = []
        for s in range(n_seg):
            xs = x[:, s * seg_len:(s + 1) * seg_len, :].clone()
            h = torch.concatenate([mem, xs], axis=1)
            q = torch.einsum('btd,dhe->bhte', h, Wq)
            k = torch.einsum('btd,dhe->bhte', h, Wk)
            v = torch.einsum('btd,dhe->bhte', h, Wv)
            scores = torch.einsum('bhqe,bhke->bhqk', q, k) * scale
            scores = torch.where(mask[None, None], scores, -1000000000.0)
            p = _softmax(scores, axis=-1)
            o = torch.einsum('bhqk,bhke->bhqe', p, v)
            o = torch.einsum('bhte,hed->btd', o, Wo)
            mem = o[:, :M, :].clone()
            outs.append(o[:, M:, :])
        return torch.concatenate(outs, axis=1)

    def _B_ref(x, w1, w2, w3, w4):
        B, S, D = x.shape
        h = _gelu(_layernorm(x, axis=-1) @ w1)
        c = D // 4
        g0 = _pad(h[:, :, 0 * c:1 * c], ((0, 0), (1, 0), (0, 0)))[:, :S, :]
        g1 = _pad(h[:, :, 1 * c:2 * c], ((0, 0), (0, 1), (0, 0)))[:, 1:, :]
        g2 = _pad(h[:, :, 2 * c:3 * c], ((0, 0), (2, 0), (0, 0)))[:, :S, :]
        g3 = _pad(h[:, :, 3 * c:], ((0, 0), (0, 2), (0, 0)))[:, 2:, :]
        hs = torch.concatenate([g0, g1, g2, g3], axis=-1) @ w2
        x1 = x + hs
        h2 = _gelu(_layernorm(x1, axis=-1) @ w3) @ w4
        return x1 + h2
    x = A_x
    xn = _layernorm(x, axis=-1)
    s = _A_ref(xn, A_mem0, A_Wq, A_Wk, A_Wv, A_Wo, A_seg_len)
    g = _silu(_B_ref(xn, B_w1, B_w2, B_w3, B_w4))
    return x + s * g
```

```cpp
#include <cuda_runtime.h>
#include <cuda_bf16.h>
#include <cuda.h>
#include <stdint.h>

typedef __nv_bfloat16 bf16;

constexpr int S_ = 2048, D_ = 1024, H_ = 32, DH_ = 128, F_ = 3584, NSEG = 64;

__device__ __align__(1024) bf16 g_xn[S_ * D_];
__device__ __align__(1024) bf16 g_xn2[S_ * D_];
__device__ __align__(1024) bf16 g_ox[S_ * H_ * DH_];
__device__ __align__(1024) bf16 g_h1[S_ * D_];
__device__ __align__(1024) bf16 g_x1[S_ * D_];
__device__ __align__(1024) bf16 g_ln1[S_ * D_];
__device__ __align__(1024) bf16 g_h3[S_ * F_];
__device__ __align__(1024) bf16 g_gate[S_ * D_];
__device__ __align__(1024) uint2 g_rstat[S_ * 4];

constexpr int XPAGE = 1 << 21;
__device__ __align__(4096) unsigned char g_xch[4 * XPAGE];
__device__ __forceinline__ uint32_t xchunk(int c, int p) { return (uint32_t)(c | ((__popc(c & 0xb3) & 1) ^ p)) << 12; }

#define TR(i)
#define TRB(i)
#define TRX(i, v)
#define TRV(i, v)
#define TG(r, i)
#define TRCAL(k)
#define ST(i)
__device__ __forceinline__ uint32_t smem_u32(const void* p) { return (uint32_t)__cvta_generic_to_shared(p); }
__device__ __forceinline__ void mbar_init(uint32_t bar, int cnt) {
  asm volatile("mbarrier.init.shared::cta.b64 [%0], %1;" ::"r"(bar), "r"(cnt) : "memory");
}
__device__ __forceinline__ void mbar_expect_tx(uint32_t bar, int bytes) {
  asm volatile("mbarrier.arrive.expect_tx.shared::cta.b64 _, [%0], %1;" ::"r"(bar), "r"(bytes) : "memory");
}
__device__ __forceinline__ void mbar_arrive(uint32_t bar) {
  asm volatile("mbarrier.arrive.shared::cta.b64 _, [%0];" ::"r"(bar) : "memory");
}
__device__ __forceinline__ void mbar_wait(uint32_t bar, uint32_t parity) {
  uint32_t ok;
  int n = 0;
  do {
    asm volatile(
        "{.reg .pred p; mbarrier.try_wait.parity.shared::cta.b64 p, [%1], %2; selp.u32 %0, 1, 0, p;}"
        : "=r"(ok) : "r"(bar), "r"(parity) : "memory");
  } while (!ok && ++n < (1 << 22));
}
__device__ __forceinline__ void mbar_wait_long(uint32_t bar, uint32_t parity) {
  uint32_t ok;
  int n = 0;
#pragma unroll 1
  do {
    asm volatile(
        "{.reg .pred p; mbarrier.try_wait.parity.shared::cta.b64 p, [%1], %2, 2000; selp.u32 %0, 1, 0, p;}"
        : "=r"(ok) : "r"(bar), "r"(parity) : "memory");
  } while (!ok && ++n < (1 << 22));
}
__device__ __forceinline__ void tma_load_2d(uint32_t dst, const CUtensorMap* m, int c0, int c1, uint32_t bar) {
  asm volatile(
      "cp.async.bulk.tensor.2d.shared::cluster.global.mbarrier::complete_tx::bytes [%0], [%1, {%3, %4}], [%2];"
      ::"r"(dst), "l"(m), "r"(bar), "r"(c0), "r"(c1) : "memory");
}
__device__ __forceinline__ void tma_load_2d_ef(uint32_t dst, const CUtensorMap* m, int c0, int c1, uint32_t bar) {
  asm volatile(
      "{.reg .b64 pol; createpolicy.fractional.L2::evict_first.b64 pol, 1.0;\n"
      "cp.async.bulk.tensor.2d.shared::cluster.global.mbarrier::complete_tx::bytes.L2::cache_hint [%0], [%1, {%3, %4}], [%2], pol;}"
      ::"r"(dst), "l"(m), "r"(bar), "r"(c0), "r"(c1) : "memory");
}
__device__ __forceinline__ void tma_load_3d(uint32_t dst, const CUtensorMap* m, int c0, int c1, int c2, uint32_t bar) {
  asm volatile(
      "cp.async.bulk.tensor.3d.shared::cluster.global.mbarrier::complete_tx::bytes [%0], [%1, {%3, %4, %5}], [%2];"
      ::"r"(dst), "l"(m), "r"(bar), "r"(c0), "r"(c1), "r"(c2) : "memory");
}
__device__ __forceinline__ void tma_store_2d(const CUtensorMap* m, uint32_t src, int c0, int c1) {
  asm volatile("cp.async.bulk.tensor.2d.global.shared::cta.bulk_group [%0, {%2, %3}], [%1];"
               ::"l"(m), "r"(src), "r"(c0), "r"(c1) : "memory");
}
__device__ __forceinline__ uint64_t policy(bool stream) {
  uint64_t a, b;
  asm("createpolicy.fractional.L2::evict_first.b64 %0, 1.0;" : "=l"(a));
  asm("createpolicy.fractional.L2::evict_normal.b64 %0, 1.0;" : "=l"(b));
  return stream ? a : b;
}
__device__ __forceinline__ void tma_store_2d_p(const CUtensorMap* m, uint32_t src, int c0, int c1, uint64_t pol) {
  asm volatile("cp.async.bulk.tensor.2d.global.shared::cta.bulk_group.L2::cache_hint [%0, {%2, %3}], [%1], %4;"
               ::"l"(m), "r"(src), "r"(c0), "r"(c1), "l"(pol) : "memory");
}
__device__ __forceinline__ void tma_prefetch_2d(const CUtensorMap* m, int c0, int c1) {
  asm volatile("cp.async.bulk.prefetch.tensor.2d.L2.global [%0, {%1, %2}];" ::"l"(m), "r"(c0), "r"(c1) : "memory");
}
__device__ __forceinline__ void tma_prefetch_3d(const CUtensorMap* m, int c0, int c1, int c2) {
  asm volatile("cp.async.bulk.prefetch.tensor.3d.L2.global [%0, {%1, %2, %3}];" ::"l"(m), "r"(c0), "r"(c1), "r"(c2) : "memory");
}
__device__ __forceinline__ uint32_t clk32() { uint32_t c; asm volatile("mov.u32 %0, %%clock;" : "=r"(c)::"memory"); return c; }
__device__ __forceinline__ uint32_t ld_rlx1(const void* p) { uint32_t v; asm volatile("ld.relaxed.gpu.global.u32 %0, [%1];" : "=r"(v) : "l"(p) : "memory"); return v; }
__device__ __forceinline__ uint32_t smid() { uint32_t c; asm volatile("mov.u32 %0, %%smid;" : "=r"(c)); return c; }
__device__ __forceinline__ void fence_async_smem() { asm volatile("fence.proxy.async.shared::cta;" ::: "memory"); }
__device__ __forceinline__ void bar_sync(int id, int n) { asm volatile("bar.sync %0, %1;" ::"r"(id), "r"(n) : "memory"); }
__device__ __forceinline__ void bar_arrive(int id, int n) { asm volatile("bar.arrive %0, %1;" ::"r"(id), "r"(n) : "memory"); }
__host__ __device__ constexpr uint64_t make_desc(uint32_t addr, uint32_t lbo, uint32_t sbo, uint32_t mode) {
  return (uint64_t)((addr & 0x3FFFF) >> 4) | ((uint64_t)(lbo >> 4) << 16) | ((uint64_t)(sbo >> 4) << 32) |
         ((uint64_t)mode << 62);
}
#define WG_FENCE() asm volatile("wgmma.fence.sync.aligned;" ::: "memory")
#define WG_COMMIT() asm volatile("wgmma.commit_group.sync.aligned;" ::: "memory")
#define WG_WAIT(n) asm volatile("wgmma.wait_group.sync.aligned " #n ";" ::: "memory")

__device__ __forceinline__ uint32_t pack_bf16(float lo, float hi) {
  uint32_t r;
  asm("cvt.rn.bf16x2.f32 %0, %1, %2;" : "=r"(r) : "f"(hi), "f"(lo));
  return r;
}
__device__ __forceinline__ float bf_lo(uint32_t v) { return __uint_as_float(v << 16); }
__device__ __forceinline__ float bf_hi(uint32_t v) { return __uint_as_float(v & 0xffff0000u); }
__device__ __forceinline__ float rbf(float x) { return __bfloat162float(__float2bfloat16_rn(x)); }

__device__ __forceinline__ void ldsm4(uint32_t* r, uint32_t a) {
  asm volatile("ldmatrix.sync.aligned.m8n8.x4.shared.b16 {%0,%1,%2,%3}, [%4];"
               : "=r"(r[0]), "=r"(r[1]), "=r"(r[2]), "=r"(r[3]) : "r"(a) : "memory");
}
__device__ __forceinline__ void ldsm4t(uint32_t* r, uint32_t a) {
  asm volatile("ldmatrix.sync.aligned.m8n8.x4.trans.shared.b16 {%0,%1,%2,%3}, [%4];"
               : "=r"(r[0]), "=r"(r[1]), "=r"(r[2]), "=r"(r[3]) : "r"(a) : "memory");
}
__device__ __forceinline__ void stsm4(uint32_t a, uint32_t r0, uint32_t r1, uint32_t r2, uint32_t r3) {
  asm volatile("stmatrix.sync.aligned.m8n8.x4.shared.b16 [%0], {%1,%2,%3,%4};"
               ::"r"(a), "r"(r0), "r"(r1), "r"(r2), "r"(r3) : "memory");
}
__device__ __forceinline__ void stsm4t(uint32_t a, uint32_t r0, uint32_t r1, uint32_t r2, uint32_t r3) {
  asm volatile("stmatrix.sync.aligned.m8n8.x4.trans.shared.b16 [%0], {%1,%2,%3,%4};"
               ::"r"(a), "r"(r0), "r"(r1), "r"(r2), "r"(r3) : "memory");
}
__device__ __forceinline__ void mma16816(float* d, uint32_t a0, uint32_t a1, uint32_t a2, uint32_t a3, uint32_t b0,
                                         uint32_t b1) {
  asm(
      "mma.sync.aligned.m16n8k16.row.col.f32.bf16.bf16.f32 {%0,%1,%2,%3}, {%4,%5,%6,%7}, {%8,%9}, {%0,%1,%2,%3};"
      : "+f"(d[0]), "+f"(d[1]), "+f"(d[2]), "+f"(d[3]) : "r"(a0), "r"(a1), "r"(a2), "r"(a3), "r"(b0), "r"(b1));
}
__device__ __forceinline__ void mma16816c(float* d, const float* c, uint32_t a0, uint32_t a1, uint32_t a2, uint32_t a3,
                                          uint32_t b0, uint32_t b1) {
  asm volatile(
      "mma.sync.aligned.m16n8k16.row.col.f32.bf16.bf16.f32 {%0,%1,%2,%3}, {%4,%5,%6,%7}, {%8,%9}, {%10,%11,%12,%13};"
      : "=f"(d[0]), "=f"(d[1]), "=f"(d[2]), "=f"(d[3])
      : "r"(a0), "r"(a1), "r"(a2), "r"(a3), "r"(b0), "r"(b1), "f"(c[0]), "f"(c[1]), "f"(c[2]), "f"(c[3]));
}
__device__ __forceinline__ void mma1688(float* d, uint32_t a0, uint32_t a1, uint32_t b0) {
  asm("mma.sync.aligned.m16n8k8.row.col.f32.bf16.bf16.f32 {%0,%1,%2,%3}, {%4,%5}, {%6}, {%0,%1,%2,%3};"
               : "+f"(d[0]), "+f"(d[1]), "+f"(d[2]), "+f"(d[3]) : "r"(a0), "r"(a1), "r"(b0));
}
__device__ __forceinline__ void wgmma_n8_tt(float* d, uint64_t a, uint64_t b, int scale_d) {
  asm volatile(
      "{.reg .pred p; setp.ne.b32 p, %6, 0;\n"
      "wgmma.mma_async.sync.aligned.m64n8k16.f32.bf16.bf16 {%0,%1,%2,%3}, %4, %5, p, 1, 1, 1, 1;}"
      : "+f"(d[0]), "+f"(d[1]), "+f"(d[2]), "+f"(d[3]) : "l"(a), "l"(b), "r"(scale_d));
}
__device__ __forceinline__ void wgmma_n256(float* d, uint64_t a, uint64_t b, int scale_d) {
  asm volatile(
      "{.reg .pred p; setp.ne.b32 p, %130, 0;\n"
      "wgmma.mma_async.sync.aligned.m64n256k16.f32.bf16.bf16 "
      "{%0,%1,%2,%3,%4,%5,%6,%7,%8,%9,%10,%11,%12,%13,%14,%15,%16,%17,%18,%19,%20,%21,%22,%23,%24,%25,%26,%27,%28,%29,%30,%31,"
      "%32,%33,%34,%35,%36,%37,%38,%39,%40,%41,%42,%43,%44,%45,%46,%47,%48,%49,%50,%51,%52,%53,%54,%55,%56,%57,%58,%59,%60,%61,%62,%63,"
      "%64,%65,%66,%67,%68,%69,%70,%71,%72,%73,%74,%75,%76,%77,%78,%79,%80,%81,%82,%83,%84,%85,%86,%87,%88,%89,%90,%91,%92,%93,%94,%95,"
      "%96,%97,%98,%99,%100,%101,%102,%103,%104,%105,%106,%107,%108,%109,%110,%111,%112,%113,%114,%115,%116,%117,%118,%119,%120,%121,%122,%123,%124,%125,%126,%127},"
      " %128, %129, p, 1, 1, 0, 1;}"
      : "+f"(d[0]), "+f"(d[1]), "+f"(d[2]), "+f"(d[3]), "+f"(d[4]), "+f"(d[5]), "+f"(d[6]), "+f"(d[7]),
        "+f"(d[8]), "+f"(d[9]), "+f"(d[10]), "+f"(d[11]), "+f"(d[12]), "+f"(d[13]), "+f"(d[14]), "+f"(d[15]),
        "+f"(d[16]), "+f"(d[17]), "+f"(d[18]), "+f"(d[19]), "+f"(d[20]), "+f"(d[21]), "+f"(d[22]), "+f"(d[23]),
        "+f"(d[24]), "+f"(d[25]), "+f"(d[26]), "+f"(d[27]), "+f"(d[28]), "+f"(d[29]), "+f"(d[30]), "+f"(d[31]),
        "+f"(d[32]), "+f"(d[33]), "+f"(d[34]), "+f"(d[35]), "+f"(d[36]), "+f"(d[37]), "+f"(d[38]), "+f"(d[39]),
        "+f"(d[40]), "+f"(d[41]), "+f"(d[42]), "+f"(d[43]), "+f"(d[44]), "+f"(d[45]), "+f"(d[46]), "+f"(d[47]),
        "+f"(d[48]), "+f"(d[49]), "+f"(d[50]), "+f"(d[51]), "+f"(d[52]), "+f"(d[53]), "+f"(d[54]), "+f"(d[55]),
        "+f"(d[56]), "+f"(d[57]), "+f"(d[58]), "+f"(d[59]), "+f"(d[60]), "+f"(d[61]), "+f"(d[62]), "+f"(d[63]),
        "+f"(d[64]), "+f"(d[65]), "+f"(d[66]), "+f"(d[67]), "+f"(d[68]), "+f"(d[69]), "+f"(d[70]), "+f"(d[71]),
        "+f"(d[72]), "+f"(d[73]), "+f"(d[74]), "+f"(d[75]), "+f"(d[76]), "+f"(d[77]), "+f"(d[78]), "+f"(d[79]),
        "+f"(d[80]), "+f"(d[81]), "+f"(d[82]), "+f"(d[83]), "+f"(d[84]), "+f"(d[85]), "+f"(d[86]), "+f"(d[87]),
        "+f"(d[88]), "+f"(d[89]), "+f"(d[90]), "+f"(d[91]), "+f"(d[92]), "+f"(d[93]), "+f"(d[94]), "+f"(d[95]),
        "+f"(d[96]), "+f"(d[97]), "+f"(d[98]), "+f"(d[99]), "+f"(d[100]), "+f"(d[101]), "+f"(d[102]), "+f"(d[103]),
        "+f"(d[104]), "+f"(d[105]), "+f"(d[106]), "+f"(d[107]), "+f"(d[108]), "+f"(d[109]), "+f"(d[110]), "+f"(d[111]),
        "+f"(d[112]), "+f"(d[113]), "+f"(d[114]), "+f"(d[115]), "+f"(d[116]), "+f"(d[117]), "+f"(d[118]), "+f"(d[119]),
        "+f"(d[120]), "+f"(d[121]), "+f"(d[122]), "+f"(d[123]), "+f"(d[124]), "+f"(d[125]), "+f"(d[126]), "+f"(d[127])
      : "l"(a), "l"(b), "r"(scale_d));
}

__device__ __forceinline__ uint4 ld_rlx4(const void* p) {
  uint4 v;
  asm volatile("{.reg .b128 r; ld.relaxed.gpu.global.b128 r, [%4]; mov.b128 {%0,%1,%2,%3}, r;}"
               : "=r"(v.x), "=r"(v.y), "=r"(v.z), "=r"(v.w) : "l"(p) : "memory");
  return v;
}
__device__ __forceinline__ uint2 ld_rlx2(const void* p) {
  uint2 v;
  asm volatile("{.reg .b64 r; ld.relaxed.gpu.global.b64 r, [%2]; mov.b64 {%0,%1}, r;}" : "=r"(v.x), "=r"(v.y) : "l"(p) : "memory");
  return v;
}
__device__ __forceinline__ void st_rlx4(void* p, uint32_t a, uint32_t b, uint32_t c, uint32_t d) {
  asm volatile("{.reg .b128 r; mov.b128 r, {%1,%2,%3,%4}; st.relaxed.gpu.global.b128 [%0], r;}"
               ::"l"(p), "r"(a), "r"(b), "r"(c), "r"(d) : "memory");
}
__device__ __forceinline__ void st_rlx2(void* p, uint32_t a, uint32_t b) {
  asm volatile("{.reg .b64 r; mov.b64 r, {%1,%2}; st.relaxed.gpu.global.b64 [%0], r;}" ::"l"(p), "r"(a), "r"(b) : "memory");
}
__device__ __forceinline__ void st_rlx1(void* p, uint32_t a) {
  asm volatile("st.relaxed.gpu.global.u32 [%0], %1;" ::"l"(p), "r"(a) : "memory");
}

__device__ __forceinline__ uint32_t nz(uint32_t v) { return v == 0u ? 0x80000000u : v; }
__device__ __forceinline__ uint32_t tagu(uint32_t v, uint32_t tag) { return (v & ~1u) | tag; }
__device__ __forceinline__ float asf(uint32_t v) { return __uint_as_float(v); }
__device__ __forceinline__ uint32_t asu(float v) { return __float_as_uint(v); }
__device__ __forceinline__ uint32_t opaque(uint32_t x) { return __shfl_sync(~0u, x, threadIdx.x & 31); }
__device__ __forceinline__ unsigned char* xptr(uint32_t lo, uint32_t hi) {
  uint64_t a;
  asm("mov.b64 %0, {%1, %2};" : "=l"(a) : "r"(lo), "r"(hi));
  return (unsigned char*)a;
}
#define DSC(lo) (uint64_t)xptr(lo, (uint32_t)(make_desc(0, 0, 1024, 1) >> 32))
__device__ __forceinline__ void reld4(uint4& v, const void* p, uint32_t m) {
  asm volatile("{.reg .pred q; setp.eq.b32 q, %5, 0; @q ld.relaxed.gpu.global.v4.b32 {%0,%1,%2,%3}, [%4];}"
               : "+r"(v.x), "+r"(v.y), "+r"(v.z), "+r"(v.w) : "l"(p), "r"(m) : "memory");
}
__device__ __forceinline__ uint32_t ne2(uint32_t a, uint32_t b, uint32_t t) {
  uint32_t r;
  asm("lop3.b32 %0, %1, %2, %3, 0x7E;" : "=r"(r) : "r"(a), "r"(b), "r"(t));
  return r;
}
__device__ __forceinline__ uint32_t or3(uint32_t a, uint32_t b, uint32_t c) {
  uint32_t r;
  asm("lop3.b32 %0, %1, %2, %3, 0xFE;" : "=r"(r) : "r"(a), "r"(b), "r"(c));
  return r;
}
__device__ __forceinline__ uint32_t after(uint32_t a, uint32_t dep, uint32_t zero) {
  uint32_t r;
  asm("lop3.b32 %0, %1, %2, %3, 0xF8;" : "=r"(r) : "r"(a), "r"(dep), "r"(zero));
  return r;
}
__device__ __forceinline__ uint32_t wait_clk(uint32_t t, int D) {
  uint32_t c = clk32();
  if ((int)(t - c) < D) t = c + D;
  while ((int)(c - t) < 0) c = clk32();
  return c;
}
__device__ __forceinline__ uint2 timer_edge() {
  uint32_t g0, g;
  int n = 0;
  asm volatile("mov.u32 %0, %%globaltimer_lo;" : "=r"(g0)::"memory");
#pragma unroll 1
  do { asm volatile("mov.u32 %0, %%globaltimer_lo;" : "=r"(g)::"memory"); } while (g == g0 && ++n < 8);
  return make_uint2(g, clk32());
}
__device__ __forceinline__ float4 lds_f4(uint32_t a) {
  float4 v;
  asm volatile("ld.shared.v4.f32 {%0,%1,%2,%3}, [%4];" : "=f"(v.x), "=f"(v.y), "=f"(v.z), "=f"(v.w) : "r"(a) : "memory");
  return v;
}
__device__ __forceinline__ uint4 lds_u4(uint32_t a) {
  uint4 v;
  asm volatile("ld.shared.v4.u32 {%0,%1,%2,%3}, [%4];" : "=r"(v.x), "=r"(v.y), "=r"(v.z), "=r"(v.w) : "r"(a) : "memory");
  return v;
}
__device__ __forceinline__ uint2 lds_u2(uint32_t a) {
  uint2 v;
  asm volatile("ld.shared.v2.u32 {%0,%1}, [%2];" : "=r"(v.x), "=r"(v.y) : "r"(a) : "memory");
  return v;
}
__device__ __forceinline__ uint32_t lds_u1(uint32_t a) {
  uint32_t v;
  asm volatile("ld.shared.u32 %0, [%1];" : "=r"(v) : "r"(a) : "memory");
  return v;
}
__device__ __forceinline__ void sts_u4(uint32_t a, uint4 v) {
  asm volatile("st.shared.v4.u32 [%0], {%1,%2,%3,%4};" ::"r"(a), "r"(v.x), "r"(v.y), "r"(v.z), "r"(v.w) : "memory");
}
__device__ __forceinline__ void sts_f4(uint32_t a, const float* d) {
  asm volatile("st.shared.v4.f32 [%0], {%1,%2,%3,%4};" ::"r"(a), "f"(d[0]), "f"(d[1]), "f"(d[2]), "f"(d[3]) : "memory");
}
__device__ __forceinline__ void sts_u2(uint32_t a, uint32_t x, uint32_t y) {
  asm volatile("st.shared.v2.u32 [%0], {%1,%2};" ::"r"(a), "r"(x), "r"(y) : "memory");
}
__device__ __forceinline__ void sts_u1(uint32_t a, uint32_t v) {
  asm volatile("st.shared.u32 [%0], %1;" ::"r"(a), "r"(v) : "memory");
}
__device__ __forceinline__ void sta4(uint32_t a, uint4 v, uint32_t bar) {
  asm volatile("st.async.shared::cluster.mbarrier::complete_tx::bytes.v4.b32 [%0], {%1,%2,%3,%4}, [%5];"
               ::"r"(a), "r"(v.x), "r"(v.y), "r"(v.z), "r"(v.w), "r"(bar) : "memory");
}
__device__ __forceinline__ void sta2(uint32_t a, uint32_t x, uint32_t y, uint32_t bar) {
  asm volatile("st.async.shared::cluster.mbarrier::complete_tx::bytes.v2.b32 [%0], {%1,%2}, [%3];" ::"r"(a), "r"(x), "r"(y), "r"(bar) : "memory");
}
__device__ __forceinline__ void sta1(uint32_t a, uint32_t x, uint32_t bar) {
  asm volatile("st.async.shared::cluster.mbarrier::complete_tx::bytes.b32 [%0], %1, [%2];" ::"r"(a), "r"(x), "r"(bar) : "memory");
}
__device__ __forceinline__ void arrive_remote(uint32_t bar) {
  asm volatile("mbarrier.arrive.shared::cluster.b64 _, [%0];" ::"r"(bar) : "memory");
}
__device__ __forceinline__ uint32_t peer_base(uint32_t sb, int rank) {
  uint32_t r;
  asm("mapa.shared::cluster.u32 %0, %1, %2;" : "=r"(r) : "r"(sb), "r"(rank));
  return r - sb;
}
__device__ __forceinline__ float ex2(float x) { float r; asm("ex2.approx.ftz.f32 %0, %1;" : "=f"(r) : "f"(x)); return r; }
__device__ __forceinline__ float rcp(float x) { float r; asm("rcp.approx.ftz.f32 %0, %1;" : "=f"(r) : "f"(x)); return r; }
__device__ __forceinline__ uint32_t min4(uint4 v) { return min(__vimin3_u32(v.x, v.y, v.z), v.w); }

__device__ __forceinline__ void softmax_e(float* sc) {
  float mx = fmaxf(fmaxf(fmaxf(sc[0], sc[1]), fmaxf(sc[2], sc[3])), fmaxf(fmaxf(sc[4], sc[5]), fmaxf(sc[6], sc[7])));
  mx = fmaxf(mx, fmaxf(sc[8], sc[9]));
  const float m1 = __shfl_xor_sync(~0u, mx, 1), m2 = __shfl_xor_sync(~0u, mx, 2), m3 = __shfl_xor_sync(~0u, mx, 3);
  mx = fmaxf(fmaxf(mx, m1), fmaxf(m2, m3));
  const float c = 0.08838834764831845f * 1.4426950408889634f, mc = -mx * c;
#pragma unroll
  for (int i = 0; i < 10; i++) sc[i] = ex2(fmaf(sc[i], c, mc));
}
__device__ __forceinline__ void sum_scores(float* sc, uint2 u0, uint2 u1, uint32_t u2, uint2 v0, uint2 v1, uint32_t v2) {
  sc[0] = bf_lo(u0.x) + bf_lo(v0.x); sc[1] = bf_hi(u0.x) + bf_hi(v0.x);
  sc[2] = bf_lo(u0.y) + bf_lo(v0.y); sc[3] = bf_hi(u0.y) + bf_hi(v0.y);
  sc[4] = bf_lo(u1.x) + bf_lo(v1.x); sc[5] = bf_hi(u1.x) + bf_hi(v1.x);
  sc[6] = bf_lo(u1.y) + bf_lo(v1.y); sc[7] = bf_hi(u1.y) + bf_hi(v1.y);
  sc[8] = bf_lo(u2) + bf_lo(v2); sc[9] = bf_hi(u2) + bf_hi(v2);
}
__device__ __forceinline__ void pv_mma(float* o0, float* o1, float* sm, const uint4* vx, const uint2* m, const uint32_t* p) {
  const uint32_t one = 0x3F803F80u;
#pragma unroll
  for (int i = 0; i < 4; i++) o0[i] = o1[i] = sm[i] = 0.f;
  mma16816(sm, one, one, one, one, p[0], p[1]);
  mma16816(o0, vx[0].x, vx[0].y, vx[0].z, vx[0].w, p[0], p[1]);
  mma16816(o1, vx[1].x, vx[1].y, vx[1].z, vx[1].w, p[0], p[1]);
  mma16816(sm, one, one, one, one, p[2], p[3]);
  mma16816(o0, vx[2].x, vx[2].y, vx[2].z, vx[2].w, p[2], p[3]);
  mma16816(o1, vx[3].x, vx[3].y, vx[3].z, vx[3].w, p[2], p[3]);
  mma1688(sm, one, one, p[4]);
  mma16816(o0, m[0].x, m[0].y, m[1].x, m[1].y, p[4], p[4]);
  mma16816(o1, m[2].x, m[2].y, m[3].x, m[3].y, p[4], p[4]);
}
#define D16(d) "+f"(d[0]), "+f"(d[1]), "+f"(d[2]), "+f"(d[3]), "+f"(d[4]), "+f"(d[5]), "+f"(d[6]), "+f"(d[7]), "+f"(d[8]), \
               "+f"(d[9]), "+f"(d[10]), "+f"(d[11]), "+f"(d[12]), "+f"(d[13]), "+f"(d[14]), "+f"(d[15])
__device__ __forceinline__ void wgmma_rs32(float* d, const uint32_t* a, uint64_t b, int scale_d) {
  asm volatile(
      "{.reg .pred p; setp.ne.b32 p, %21, 0;\n"
      "wgmma.mma_async.sync.aligned.m64n32k16.f32.bf16.bf16 {%0,%1,%2,%3,%4,%5,%6,%7,%8,%9,%10,%11,%12,%13,%14,%15}, "
      "{%16,%17,%18,%19}, %20, p, 1, 1, 0;}"
      : D16(d) : "r"(a[0]), "r"(a[1]), "r"(a[2]), "r"(a[3]), "l"(b), "r"(scale_d));
}
__device__ __forceinline__ void wgmma_ss32(float* d, uint64_t a, uint64_t b, int scale_d) {
  asm volatile(
      "{.reg .pred p; setp.ne.b32 p, %18, 0;\n"
      "wgmma.mma_async.sync.aligned.m64n32k16.f32.bf16.bf16 {%0,%1,%2,%3,%4,%5,%6,%7,%8,%9,%10,%11,%12,%13,%14,%15}, "
      "%16, %17, p, 1, 1, 1, 0;}"
      : D16(d) : "l"(a), "l"(b), "r"(scale_d));
}
__device__ __forceinline__ void wgmma_ss48(float* d, uint64_t a, uint64_t b, int scale_d) {
  asm volatile(
      "{.reg .pred p; setp.ne.b32 p, %26, 0;\n"
      "wgmma.mma_async.sync.aligned.m64n48k16.f32.bf16.bf16 {%0,%1,%2,%3,%4,%5,%6,%7,%8,%9,%10,%11,%12,%13,%14,%15,"
      "%16,%17,%18,%19,%20,%21,%22,%23}, %24, %25, p, 1, 1, 0, 0;}"
      : D16(d), "+f"(d[16]), "+f"(d[17]), "+f"(d[18]), "+f"(d[19]), "+f"(d[20]), "+f"(d[21]), "+f"(d[22]), "+f"(d[23])
      : "l"(a), "l"(b), "r"(scale_d));
}
enum { T_W1, T_W2, T_W3, T_W4, T_WO };
constexpr int NPAIR = 18, G_STAGES = 4, G_STAGE_BYTES = 49152, G_STG = G_STAGES * G_STAGE_BYTES, G_BAR = G_STG + 32768,
              G_SMEM = G_BAR + 256;
constexpr int WAIT_LIM = 1 << 22;
#define NSLP 40
enum { C_H1 = 0, C_LN1 = 16, C_H3 = 32, C_G = 48, C_OX = 64, C_LN = 128, C_CHK, C_DONE, C_END };
__device__ __align__(128) unsigned g_cnt[C_END * 8];

struct GemmMaps { CUtensorMap a[5], b[5], c[6], e[4], wd, od; };
__constant__ unsigned short c_list[NPAIR][24] = {
    {0x400, 0xf0, 0x51, 0xa9, 0x30a, 0x312, 0x62, 0x34a, 0x2ba, 0xc3, 0x23, 0xb3, 0x47b, 0x8000, 0x8000, 0x8000, 0x8000, 0x8000, 0x8000, 0x8000, 0x8000, 0x8000, 0x8000, 0x38},
    {0x440, 0xb0, 0x91, 0x2, 0x242, 0x31a, 0x2aa, 0x2da, 0x1a2, 0x122, 0x2ea, 0x16a, 0xdb, 0x3b, 0x2c, 0x8000, 0x8000, 0x8000, 0x8000, 0x8000, 0x8000, 0x8000, 0x8000, 0x38},
    {0x480, 0x41, 0xa1, 0x79, 0x10a, 0x1aa, 0x132, 0x13, 0x9b, 0x8c, 0x4ec, 0x8000, 0x8000, 0x8000, 0x8000, 0x8000, 0x8000, 0x8000, 0x8000, 0x8000, 0x8000, 0x8000, 0x8000, 0x38},
    {0x4c0, 0xc1, 0x61, 0x39, 0x28a, 0x1d2, 0x22a, 0x18a, 0x53, 0x5b, 0xf3, 0x4ac, 0x8000, 0x8000, 0x8000, 0x8000, 0x8000, 0x8000, 0x8000, 0x8000, 0x8000, 0x8000, 0x8000, 0x38},
    {0x408, 0x4a0, 0x21, 0x31, 0x82, 0x302, 0x26a, 0x93, 0x8b, 0x2b, 0x473, 0x8000, 0x8000, 0x8000, 0x8000, 0x8000, 0x8000, 0x8000, 0x8000, 0x8000, 0x8000, 0x8000, 0x8000, 0x30},
    {0x448, 0x78, 0x89, 0x342, 0x352, 0xa, 0x252, 0x23a, 0x2a, 0x162, 0x1e2, 0x1fa, 0xb2, 0x54, 0xc, 0x8000, 0x8000, 0x8000, 0x8000, 0x8000, 0x8000, 0x8000, 0x8000, 0x30},
    {0x488, 0x4e8, 0x59, 0xf1, 0x9a, 0x5a, 0x14a, 0xe2, 0x2fa, 0x43, 0x44, 0xdc, 0x8000, 0x8000, 0x8000, 0x8000, 0x8000, 0x8000, 0x8000, 0x8000, 0x8000, 0x8000, 0x8000, 0x30},
    {0x4c8, 0x468, 0x29, 0x35a, 0x202, 0xda, 0x272, 0x19a, 0xea, 0x94, 0xa3, 0x4eb, 0x8000, 0x8000, 0x8000, 0x8000, 0x8000, 0x8000, 0x8000, 0x8000, 0x8000, 0x8000, 0x8000, 0x30},
    {0x410, 0x70, 0xd1, 0xe9, 0x2ca, 0x182, 0x6a, 0x13a, 0x72, 0x32a, 0x17a, 0x27a, 0xba, 0x4c, 0x84, 0x8000, 0x8000, 0x8000, 0x8000, 0x8000, 0x8000, 0x8000, 0x8000, 0x30},
    {0x450, 0xf8, 0x9, 0x142, 0x4a, 0x52, 0x7a, 0x20a, 0x1f2, 0x2b2, 0xcb, 0x63, 0x49c, 0x8000, 0x8000, 0x8000, 0x8000, 0x8000, 0x8000, 0x8000, 0x8000, 0x8000, 0x8000, 0x30},
    {0x490, 0x1, 0x99, 0xb1, 0x192, 0x112, 0x37a, 0x32, 0x362, 0xb, 0x4, 0x64, 0x8000, 0x8000, 0x8000, 0x8000, 0x8000, 0x8000, 0x8000, 0x8000, 0x8000, 0x8000, 0x8000, 0x30},
    {0x4d0, 0x4e0, 0x19, 0x71, 0xca, 0x152, 0x11a, 0x24a, 0xfa, 0x222, 0x1b, 0xab, 0x433, 0x8000, 0x8000, 0x8000, 0x8000, 0x8000, 0x8000, 0x8000, 0x8000, 0x8000, 0x8000, 0x30},
    {0x418, 0xc9, 0xc2, 0x12, 0x2d2, 0x12a, 0x8a, 0x1a, 0x83, 0x3a, 0xe3, 0x424, 0x8000, 0x8000, 0x8000, 0x8000, 0x8000, 0x8000, 0x8000, 0x8000, 0x8000, 0x8000, 0x8000, 0x30},
    {0x458, 0x4a8, 0xd9, 0xb9, 0x212, 0x102, 0x33a, 0x25a, 0x172, 0x4b, 0x14, 0xa4, 0x8000, 0x8000, 0x8000, 0x8000, 0x8000, 0x8000, 0x8000, 0x8000, 0x8000, 0x8000, 0x8000, 0x30},
    {0x498, 0xb8, 0x11, 0x42, 0x292, 0x322, 0x2a2, 0x262, 0x21a, 0x15a, 0xaa, 0x1ba, 0x1b2, 0xcc, 0x4e4, 0x8000, 0x8000, 0x8000, 0x8000, 0x8000, 0x8000, 0x8000, 0x8000, 0x30},
    {0x4d8, 0x30, 0x49, 0x2c2, 0xd2, 0x282, 0x1ca, 0x2e2, 0x232, 0x29a, 0xf2, 0xc4, 0xfb, 0x4bb, 0x8000, 0x8000, 0x8000, 0x8000, 0x8000, 0x8000, 0x8000, 0x8000, 0x8000, 0x30},
    {0x420, 0x428, 0x438, 0x69, 0x92, 0x1ea, 0x22, 0x5da, 0x2f2, 0x3, 0x372, 0x5c, 0x6b, 0x34, 0x8000, 0x8000, 0x8000, 0x8000, 0x8000, 0x8000, 0x8000, 0x8000, 0x8000, 0x40},
    {0x460, 0x81, 0xe1, 0xf9, 0x1c2, 0xa2, 0x36a, 0x332, 0xd3, 0xd4, 0x1c, 0x6c, 0x8000, 0x8000, 0x8000, 0x8000, 0x8000, 0x8000, 0x8000, 0x8000, 0x8000, 0x8000, 0x8000, 0x40},
};
struct Tile { int valid, ty, mp, nt, flush, nkb; };
__device__ __forceinline__ Tile get_tile(int cl, int r) {
  const int v = c_list[cl][r];
  Tile t;
  t.valid = v < 0x8000; t.ty = v & 7; t.mp = (v >> 3) & 7; t.nt = (v >> 6) & 15; t.flush = (v >> 10) & 1;
  t.nkb = t.ty == T_W4 ? 56 : (t.ty == T_WO ? 64 : 16);
  return t;
}
__device__ __forceinline__ unsigned ld_acq(int c) {
  unsigned v;
  asm volatile("ld.acquire.gpu.global.u32 %0, [%1];" : "=r"(v) : "l"(g_cnt + c * 8) : "memory");
  return v;
}
__device__ __forceinline__ void wait_cnt(int c, unsigned target) {
  unsigned v;
  int n = 0;
#pragma unroll 1
  do {
    v = ld_acq(c);
    if (v >= target) break;
    __nanosleep(NSLP);
  } while (++n < WAIT_LIM);
}
__device__ __forceinline__ void sig_cnt(int c, int v = 1) {
  asm volatile("red.release.gpu.global.add.u32 [%0], %1;" ::"l"(g_cnt + c * 8), "r"(v) : "memory");
}
__device__ __forceinline__ void fence_async_all() { asm volatile("fence.proxy.async.global;" ::: "memory"); }
__device__ __forceinline__ void arrive_both(uint32_t bar) {
  asm volatile(
      "{.reg .b32 r0, r1; mapa.shared::cluster.u32 r0, %0, 0; mapa.shared::cluster.u32 r1, %0, 1;\n"
      "mbarrier.arrive.shared::cluster.b64 _, [r0];\n"
      "mbarrier.arrive.shared::cluster.b64 _, [r1];}" ::"r"(bar) : "memory");
}
__device__ __forceinline__ void load_b(uint32_t dst, const CUtensorMap* m, int k, int ng, uint32_t bar) {
  asm volatile(
      "cp.async.bulk.tensor.3d.shared::cluster.global.mbarrier::complete_tx::bytes.multicast::cluster [%0], [%1, {%3, %4, %5}], [%2], %6;"
      ::"r"(dst), "l"(m), "r"(bar), "r"(0), "r"(k), "r"(ng), "h"((uint16_t)3) : "memory");
}
__device__ __forceinline__ float gelu_f(float x) {
  float u = x * (0.7978845608f + 0.0356774081f * x * x), t;
  asm("tanh.approx.f32 %0, %1;" : "=f"(t) : "f"(u));
  float hx = 0.5f * x;
  return fmaf(hx, t, hx);
}
__device__ __forceinline__ float silu_f(float x) {
  float hx = 0.5f * x, t;
  asm("tanh.approx.f32 %0, %1;" : "=f"(t) : "f"(hx));
  return fmaf(hx, t, hx);
}

__device__ __forceinline__ uint32_t add2(uint32_t a, uint32_t b) { uint32_t r; asm("add.rn.bf16x2 %0, %1, %2;" : "=r"(r) : "r"(a), "r"(b)); return r; }
__device__ __forceinline__ uint32_t mul2(uint32_t a, uint32_t b) { uint32_t r; asm("mul.rn.bf16x2 %0, %1, %2;" : "=r"(r) : "r"(a), "r"(b)); return r; }

__device__ __forceinline__ uint32_t scale2(uint32_t d, uint32_t hi, uint32_t lo) {
  uint32_t r;
  asm("fma.rn.bf16x2 %0, %1, %2, %3;" : "=r"(r) : "r"(d), "r"(hi), "r"(mul2(d, lo)));
  return r;
}
__device__ __forceinline__ void split2(float s, uint32_t& hi, uint32_t& lo) {
  hi = pack_bf16(s, s);
  const float r = s - bf_lo(hi);
  lo = pack_bf16(r, r);
}
__device__ __forceinline__ float ln_inv(float m2) {
  float sd, inv;
  asm("sqrt.approx.f32 %0, %1;" : "=f"(sd) : "f"(rbf(rbf(m2 * (1.f / 1024.f)) + 1e-5f)));
  asm("rcp.approx.f32 %0, %1;" : "=f"(inv) : "f"(rbf(sd)));
  return inv;
}
__device__ __forceinline__ void ln_packed(uint32_t* u) {
  float s = 0.f, s2 = 0.f;
#pragma unroll
  for (int i = 0; i < 16; i++) { s += bf_lo(u[i]); s2 += bf_hi(u[i]); }
  s += s2;
#pragma unroll
  for (int o = 16; o > 0; o >>= 1) s += __shfl_xor_sync(~0u, s, o);
  float mean = s * (1.f / 1024.f), q = 0.f, q2 = 0.f;
#pragma unroll
  for (int i = 0; i < 16; i++) { float a = bf_lo(u[i]) - mean, b = bf_hi(u[i]) - mean; q = fmaf(a, a, q); q2 = fmaf(b, b, q2); }
  q += q2;
#pragma unroll
  for (int o = 16; o > 0; o >>= 1) q += __shfl_xor_sync(~0u, q, o);
  const uint32_t nmb = pack_bf16(-mean, -mean);
  uint32_t hi, lo;
  split2(ln_inv(q), hi, lo);
#pragma unroll
  for (int i = 0; i < 16; i++) u[i] = scale2(add2(u[i], nmb), hi, lo);
}
__device__ __forceinline__ void row_ld(uint32_t* u, const bf16* p, int lane) {
#pragma unroll
  for (int i = 0; i < 4; i++) {
    uint4 v = __ldcg((const uint4*)(p + i * 256 + lane * 8));
    u[i * 4] = v.x; u[i * 4 + 1] = v.y; u[i * 4 + 2] = v.z; u[i * 4 + 3] = v.w;
  }
}
__device__ __forceinline__ void row_st(const uint32_t* u, bf16* p, int lane) {
#pragma unroll
  for (int i = 0; i < 4; i++) *(uint4*)(p + i * 256 + lane * 8) = make_uint4(u[i * 4], u[i * 4 + 1], u[i * 4 + 2], u[i * 4 + 3]);
}

__device__ __forceinline__ void epi_chunk(uint32_t* pk, int c, int act, uint32_t buf, uint32_t xo, const CUtensorMap* cm,
                                          int col, int row, int lane) {
  if (act == T_W1 || act == T_W3) {
#pragma unroll
    for (int i = 0; i < 8; i++) pk[i] = pack_bf16(gelu_f(bf_lo(pk[i])), gelu_f(bf_hi(pk[i])));
  } else if (act == T_W4) {
#pragma unroll
    for (int i = 0; i < 8; i++) pk[i] = pack_bf16(silu_f(bf_lo(pk[i])), silu_f(bf_hi(pk[i])));
  }
  const uint32_t bf = buf + (c & 2) * 1024;
  if (!(c & 1)) {
    if (lane == 0) asm volatile("cp.async.bulk.wait_group.read 1;" ::: "memory");
    __syncwarp();
  }
  const uint32_t x2 = xo ^ ((c & 1) << 6);
  stsm4(bf + x2, pk[0], pk[1], pk[2], pk[3]);
  stsm4(bf + (x2 ^ 32), pk[4], pk[5], pk[6], pk[7]);
  if (c & 1) {
    fence_async_smem();
    __syncwarp();
    if (lane == 0) {
      tma_store_2d(cm, bf, col + (c >> 1) * 64, row);
      asm volatile("cp.async.bulk.commit_group;" ::: "memory");
    }
  }
}

#define DX 0
constexpr int NRD = 5, D_STAGES = 6, D_W = 0, D_RING = 2 * (8 - NRD) * 16384, D_IN = D_RING + D_STAGES * 16384;
static_assert(D_IN + 32768 <= G_BAR, "smem");

__global__ void __cluster_dims__(2, 1, 1) __launch_bounds__(384, 1)
k_gemm(const __grid_constant__ GemmMaps maps, const bf16* __restrict__ x, bf16* __restrict__ out) {
  extern __shared__ __align__(1024) unsigned char smem_raw[];
  const uint32_t sb = smem_u32(smem_raw);
  const int tid = threadIdx.x, wid = __shfl_sync(~0u, tid >> 5, 0), wg = wid >> 2, w = wid & 3, lane = tid & 31;
  const int rank = blockIdx.x & 1, cl = blockIdx.x >> 1;
  const uint32_t bFull = sb + G_BAR, bEmpty = bFull + 32, bPub = bFull + 64, dFull = bFull + 72, dEmpty = dFull + 48, dW = dEmpty + 48, dIn = dW + 8, dReady = dIn + 32;
  if (tid >= 32 && tid < 32 + 22) asm volatile("prefetch.tensormap [%0];" ::"l"(&maps.a[0] + (tid - 32)) : "memory");
  if (tid == 0) {
    TG(95, 0);
    if (sb & 1023) __trap();
    for (int i = 0; i < G_STAGES; i++) { mbar_init(bFull + i * 8, 1); mbar_init(bEmpty + i * 8, 4); }
    for (int i = 0; i < D_STAGES; i++) { mbar_init(dFull + i * 8, 1); mbar_init(dEmpty + i * 8, 2); }
    for (int i = 0; i < 5; i++) mbar_init(dW + i * 8, 1);
    mbar_init(bPub, 8);
    sts_u1(dReady, 0);
    asm volatile("fence.mbarrier_init.release.cluster;" ::: "memory");
  }
  __syncthreads();
  asm volatile("barrier.cluster.arrive.relaxed.aligned;" ::: "memory");
#define CLUSTER_SYNC() asm volatile("barrier.cluster.arrive.aligned; barrier.cluster.wait.aligned;" ::: "memory")
  if (wg == 2) {
    asm volatile("setmaxnreg.dec.sync.aligned.u32 40;");
    asm volatile("barrier.cluster.wait.aligned;" ::: "memory");
    if (w == 0 && lane == 0) {
      int st = 0, ph = 1;
      for (int r = 0;; r++) {
        const Tile t = get_tile(cl, r);
        if (!t.valid) break;
        const int mt = t.mp * 2 + rank;
        const CUtensorMap *am = &maps.a[t.ty], *bm = &maps.b[t.ty];
        if (r == 0) {
          for (int kb = 0; kb < G_STAGES; kb++) {
            mbar_expect_tx(bFull + kb * 8, G_STAGE_BYTES);
            load_b(sb + kb * G_STAGE_BYTES + 16384 + rank * 16384, bm, kb * 64, t.nt * 4 + rank * 2, bFull + kb * 8);
          }
        }
        if (t.ty == T_W1) wait_cnt(C_LN, 96);
        else if (t.ty == T_W2) { wait_cnt(C_H1 + mt, 4); if (mt > 0) wait_cnt(C_H1 + mt - 1, 4); if (mt < 15) wait_cnt(C_H1 + mt + 1, 4); }
        else if (t.ty == T_W3) wait_cnt(C_LN1 + mt, 4);
        else if (t.ty == T_W4) wait_cnt(C_H3 + mt, 14);
        else wait_cnt(C_OX + mt * 4 + 3, 128);
        fence_async_all();
        TG(r, 0);
        if (r == 0 && cl == 0) ST(5);
        for (int kb = 0; kb < t.nkb; kb++) {
          const bool early = r == 0 && kb < G_STAGES;
          mbar_wait(bEmpty + st * 8, ph);
          const uint32_t full = bFull + st * 8, sa = sb + st * G_STAGE_BYTES;
          if (!early) mbar_expect_tx(full, G_STAGE_BYTES);
          int roff = 0;
          if (t.ty == T_W2) { int gq = kb >> 2; roff = (gq & 1) ? (gq >> 1) + 1 : -((gq >> 1) + 1); }
          tma_load_2d(sa, am, kb * 64, mt * 128 + roff, full);
          if (!early) load_b(sa + 16384 + rank * 16384, bm, kb * 64, t.nt * 4 + rank * 2, full);
          if (++st == G_STAGES) { st = 0; ph ^= 1; }
        }
        if (t.ty == T_WO) { wait_cnt(C_G + mt, 4); fence_async_all(); }
        for (int i = 0; i < (t.ty == T_WO ? 4 : (t.ty & 1) * 2); i++) {
          const CUtensorMap* em = &maps.e[(t.ty >> 1) + (i >> 1)];
          const int col = t.nt * 256 + (i & 1) * 128;
          mbar_wait(bEmpty + st * 8, ph);
          const uint32_t full = bFull + st * 8, sa = sb + st * G_STAGE_BYTES;
          mbar_expect_tx(full, 32768);
          tma_load_2d(sa, em, col, mt * 128, full);
          tma_load_2d(sa + 16384, em, col + 64, mt * 128, full);
          if (++st == G_STAGES) { st = 0; ph ^= 1; }
        }
      }
      if (c_list[cl][23] < NSEG) {
        for (int i = 0; i < G_STAGES; i++) {
          mbar_wait(bEmpty + st * 8, ph);
          if (++st == G_STAGES) { st = 0; ph ^= 1; }
        }
        mbar_expect_tx(dW, D_RING);
        for (int i = 0; i < 2 * D_STAGES; i++) {
          if (!(i & 1)) mbar_expect_tx(dFull + i * 4, 16384);
          tma_load_2d(sb + D_RING + i * 8192, &maps.wd, cl * 64, rank * 2048 + (i & 1) * 1024 + (i >> 1) * 64, dFull + (i >> 1) * 8);
        }
        for (int q = 0; q < 4 * (8 - NRD); q++)
          tma_load_2d(sb + D_W + q * 8192, &maps.wd, cl * 64, rank * 2048 + (q >= 2 * (8 - NRD) ? 2 : 1) * NRD * 128 + q * 64, dW);
      }
    } else if (w == 3 && lane == 0) {
      int ph = 0;
      for (int r = 0;; r++) {
        const Tile t = get_tile(cl, r);
        if (!t.valid) break;
        if (t.ty != T_WO) { mbar_wait_long(bPub, ph); ph ^= 1; sig_cnt(t.ty * 16 + t.mp * 2 + rank); TG(r, 3); }
      }
    }
    __syncwarp();
    CLUSTER_SYNC();
    const int s0 = c_list[cl][23];
    if (w == 0 && lane == 0 && s0 < NSEG) {
      int st = 0, ph = 0, ready = s0;
      for (int i = D_STAGES; i < 2 * NRD + 8 * (NSEG - s0); i++) {
        const int n = i - 2 * NRD, s = s0 + (n >> 3);
        if (s >= ready) {
#pragma unroll 1
          for (int it = 0; s >= ready && it < 64 * WAIT_LIM; it++)
            asm volatile("ld.acquire.cta.shared.u32 %0, [%1];" : "=r"(ready) : "r"(dReady) : "memory");
          fence_async_all();
          TG(24 + s, 0);
        }
        mbar_wait(dEmpty + st * 8, ph);
        const uint32_t full = dFull + st * 8, sa = sb + D_RING + st * 16384;
        mbar_expect_tx(full, 16384);
        if (n < 0) {
          for (int g = 0; g < 2; g++) tma_load_2d(sa + g * 8192, &maps.wd, cl * 64, rank * 2048 + g * 1024 + i * 64, full);
        } else {
          asm volatile(
              "cp.async.bulk.tensor.4d.shared::cluster.global.mbarrier::complete_tx::bytes [%0], [%1, {%3, %4, %5, %6}], [%2];"
              ::"r"(sa), "l"(&maps.od), "r"(full), "r"(0), "r"(s * 32), "r"((n & 7) * 2), "r"(rank * 2) : "memory");
        }
        if (++st == D_STAGES) { st = 0; ph ^= 1; }
      }
    } else if (w == 1) {
      int ready = s0;
#pragma unroll 1
      for (int it = 0; ready < NSEG; it++) {
        const int q = min(ready + lane, NSEG - 1);
        const bool ok = (lane < 8 && ld_acq(C_OX + q) >= 128 && ld_acq(C_G + (q >> 2)) >= 4) || it > WAIT_LIM;
        const int n = __ffs(~__ballot_sync(~0u, ok && lane < 8)) - 1;
        ready += n;
        __syncwarp();
        if (n == 0) __nanosleep(NSLP);
        else if (lane == 0) asm volatile("st.release.cta.shared.u32 [%0], %1;" ::"r"(dReady), "r"(ready) : "memory");
      }
      uint32_t last = 0;
      if (lane == 0) asm volatile("atom.acq_rel.gpu.global.inc.u32 %0, [%1], %2;" : "=r"(last) : "l"(g_cnt + C_DONE * 8), "r"(gridDim.x - 1) : "memory");
      if (__shfl_sync(~0u, last, 0) == gridDim.x - 1)
        for (int i = lane; i < C_DONE; i += 32) g_cnt[i * 8] = 0;
    }
    __syncwarp();
  } else {
    asm volatile("setmaxnreg.inc.sync.aligned.u32 232;");
    asm volatile("barrier.cluster.wait.aligned;" ::: "memory");
    const bool leader = (tid & 127) == 0;
    {
      const int rr = (lane & 7) + ((lane >> 3) & 1) * 8;
      const uint32_t xo = rr * 128 + (((lane >> 4) ^ (rr & 7)) << 4), buf = sb + G_STG + wid * 4096, erow = wid * 2048;
      int st = 0, ph = 0, r = 0;
      uint32_t pk[64];
      int dact = -1, dcol = 0, drow = 0;
      bool pend = false, hold = false, flush = false;
      const CUtensorMap* dcm = nullptr;
      float acc[128];
      while (true) {
        const Tile t = get_tile(cl, r);
        const int mt = t.mp * 2 + rank;
        const bool run = t.valid && !hold;
        int prev = 0;
#define KBLOCK(kb)                                                                                      \
  {                                                                                                     \
    mbar_wait(bFull + st * 8, ph);                                                                      \
    uint32_t sa = sb + st * G_STAGE_BYTES;                                                              \
    uint64_t da = make_desc(sa + wg * 8192, 16, 1024, 1), db = make_desc(sa + 16384, 8192, 1024, 1);    \
    WG_FENCE();                                                                                         \
    _Pragma("unroll") for (int k = 0; k < 4; k++) wgmma_n256(acc, da + k * 2, db + k * 128, ((kb) | k) != 0); \
    WG_COMMIT();                                                                                        \
    if ((kb) > 0) { WG_WAIT(1); if (leader) arrive_both(bEmpty + prev * 8); }                           \
    prev = st;                                                                                          \
    if (++st == G_STAGES) { st = 0; ph ^= 1; }                                                          \
  }
#define PUBLISH()                                                                                       \
  {                                                                                                     \
    if (lane == 0) { asm volatile("cp.async.bulk.wait_group 0;" ::: "memory"); if (pend) mbar_arrive(bPub); } \
    __syncwarp();                                                                                       \
  }
#pragma unroll
        for (int kb = 0; kb < 8; kb++) {
          if (run) KBLOCK(kb);
          if (run && kb == 0 && tid == 0) TG(r, 1);
          if (dact >= 0) epi_chunk(pk + kb * 8, kb, dact, buf, xo, dcm, dcol, drow, lane);
        }
        if (!run) {
          WG_WAIT(0);
          if (dact != T_W2) {
            PUBLISH();
            if (!t.valid) break;
            dact = -1; pend = hold = false;
            continue;
          }
          const uint2* sp = g_rstat + (drow + (lane >> 2)) * 4 + (lane & 3);
          uint2 q[2];
          for (int n = 0; n < WAIT_LIM; n++) {
            q[0] = ld_rlx2(sp); q[1] = ld_rlx2(sp + 32);
            if (!__any_sync(~0u, q[0].y == 0u || q[1].y == 0u)) break;
          }
          uint32_t nmb[2], hi[2], lo[2];
#pragma unroll
          for (int e = 0; e < 2; e++) {
            const float sp = __uint_as_float(q[e].x);
            float a = sp + __shfl_xor_sync(~0u, sp, 1);
            a += __shfl_xor_sync(~0u, a, 2);
            const float mean = a * (1.f / 1024.f), dm = sp * (1.f / 256.f) - mean;
            float v = fmaf(256.f * dm, dm, __uint_as_float(q[e].y & 0x7fffffffu));
            v += __shfl_xor_sync(~0u, v, 1);
            v += __shfl_xor_sync(~0u, v, 2);
            nmb[e] = pack_bf16(-mean, -mean);
            split2(ln_inv(v), hi[e], lo[e]);
          }
#pragma unroll
          for (int i = 0; i < 64; i++) pk[i] = scale2(add2(pk[i], nmb[i & 1]), hi[i & 1], lo[i & 1]);
          dact = T_WO;
          dcm = &maps.c[5];
          hold = flush;
          continue;
        }
#pragma unroll 1
        for (int kb = 8; kb < t.nkb; kb++) {
          KBLOCK(1);
          if (kb == 9 && pend) PUBLISH();
        }
        WG_WAIT(0);
        if (leader) arrive_both(bEmpty + prev * 8);
        if (tid == 0) TG(r, 2);
#pragma unroll
        for (int i = 0; i < 64; i++) pk[i] = pack_bf16(acc[2 * i], acc[2 * i + 1]);
#define EOPERAND(hh, OP)                                                                   \
  {                                                                                        \
    mbar_wait(bFull + st * 8, ph);                                                         \
    const uint32_t eb = sb + st * G_STAGE_BYTES + erow;                                    \
    _Pragma("unroll") for (int q = 0; q < 8; q++) {                                        \
      uint32_t a[4];                                                                       \
      ldsm4(a, eb + (q >> 2) * 16384 + (xo ^ ((q & 3) << 5)));                             \
      _Pragma("unroll") for (int i = 0; i < 4; i++) pk[hh * 32 + q * 4 + i] = OP(pk[hh * 32 + q * 4 + i], a[i]); \
    }                                                                                      \
    bar_sync(1 + wg, 128);                                                                 \
    if (leader) arrive_both(bEmpty + st * 8);                                              \
    if (++st == G_STAGES) { st = 0; ph ^= 1; }                                             \
  }
        if (t.ty == T_WO) { EOPERAND(0, mul2); EOPERAND(1, mul2); }
        if (t.ty != T_W1 && t.ty != T_W3) { EOPERAND(0, add2); EOPERAND(1, add2); }
        uint2* sp = g_rstat + (mt * 128 + wid * 16 + (lane >> 2)) * 4 + t.nt;
        if (t.ty == T_W2) {
          const uint32_t one = 0x3F803F80u;
          float *sm = acc, *s2 = acc + 4, *q0 = acc + 8, *q1 = acc + 12;
#pragma unroll
          for (int i = 0; i < 32; i++) acc[i] = 0.f;
#pragma unroll
          for (int i = 0; i < 64; i += 4) mma16816((i & 4) ? s2 : sm, pk[i], pk[i + 1], pk[i + 2], pk[i + 3], one, one);
          sm[0] += s2[0]; sm[2] += s2[2];
          const uint32_t c0 = pack_bf16(sm[0] * (-1.f / 256.f), sm[0] * (-1.f / 256.f)), c1 = pack_bf16(sm[2] * (-1.f / 256.f), sm[2] * (-1.f / 256.f));
#pragma unroll
          for (int i = 0; i < 64; i += 4) {
            const uint32_t a0 = add2(pk[i], c0), a1 = add2(pk[i + 1], c1), a2 = add2(pk[i + 2], c0), a3 = add2(pk[i + 3], c1);
            mma16816(q0, a0, a1, a2, a3, a0, a2);
            mma16816(q1, a0, a1, a2, a3, a1, a3);
          }
          if ((lane >> 3) == (lane & 3)) {
            const float e0 = fmaf(sm[0], 1.f / 256.f, bf_lo(c0)), e1 = fmaf(sm[2], 1.f / 256.f, bf_lo(c1));
            const float m0 = fmaxf(fmaf(-256.f * e0, e0, (lane & 4) ? q0[1] : q0[0]), 0.f);
            const float m1 = fmaxf(fmaf(-256.f * e1, e1, (lane & 4) ? q1[3] : q1[2]), 0.f);
            st_rlx2(sp, __float_as_uint(sm[0]), __float_as_uint(m0) | 0x80000000u);
            st_rlx2(sp + 32, __float_as_uint(sm[2]), __float_as_uint(m1) | 0x80000000u);
          }
          __syncwarp();
        }
        if (t.ty == T_W4 && (lane & 3) == 0) { st_rlx2(sp, 0, 0); st_rlx2(sp + 32, 0, 0); }
        dact = t.ty; dcol = t.nt * 256; drow = mt * 128 + wid * 16; dcm = &maps.c[t.ty];
        pend = t.ty != T_WO; flush = t.flush; hold = flush || t.ty == T_W2;
        r++;
      }
    }
    CLUSTER_SYNC();
    if (tid == 0) { TG(95, 1); ST(8 + cl); }
    const int s0 = c_list[cl][23];
    if (s0 < NSEG) {
      uint32_t W[NRD * 8][4];
      int st = 0, ph = 0;
      const uint32_t xw = sb + D_RING + wg * 8192 + ((lane >> 4) * 8 + (lane & 7)) * 128 + (((w * 2 + ((lane >> 3) & 1)) ^ (lane & 7)) << 4);
#pragma unroll
      for (int i = 0; i < 2 * NRD; i++) {
        mbar_wait(dFull + st * 8, ph);
#pragma unroll
        for (int k = 0; k < 4; k++) ldsm4t(W[i * 4 + k], xw + st * 16384 + k * 2048);
        bar_sync(1 + wg, 128);
        if (leader) mbar_arrive(dEmpty + st * 8);
        if (++st == D_STAGES) { st = 0; ph ^= 1; }
      }
      mbar_wait(dW, 0);
      if (tid == 0) TG(95, 2);
      const int q = rank * 2 + wg;
      const uint32_t in = sb + D_IN + (tid & 127) * 16, p0 = peer_base(sb, 0), p1 = peer_base(sb, 1);
      const size_t eo = (size_t)(q * 8 + (lane >> 2)) * D_ + cl * 64 + w * 16 + (lane & 3) * 2;
      uint32_t e[4] = {}, dA = (uint32_t)make_desc(sb + D_W + wg * (D_RING / 2), 1024, 1024, 1);
      const uint32_t dB = (uint32_t)make_desc(sb + D_RING + wg * 8192, 16, 1024, 1);
#define FINISH(s)                                                                                        \
  {                                                                                                      \
    const uint32_t b = (s) & 1, a = in + wg * 16384 + b * 8192;                                          \
    mbar_wait(dIn + (wg * 2 + b) * 8, (((s) - s0) >> 1) & 1);                                            \
    const float4 v0 = lds_f4(a), v1 = lds_f4(a + 2048), v2 = lds_f4(a + 4096), v3 = lds_f4(a + 6144);    \
    uint32_t u0 = pack_bf16((v0.x + v1.x) + (v2.x + v3.x), (v0.y + v1.y) + (v2.y + v3.y));               \
    uint32_t u1 = pack_bf16((v0.z + v1.z) + (v2.z + v3.z), (v0.w + v1.w) + (v2.w + v3.w));               \
    asm volatile("movmatrix.sync.aligned.m8n8.trans.b16 %0, %0;" : "+r"(u0));                            \
    asm volatile("movmatrix.sync.aligned.m8n8.trans.b16 %0, %0;" : "+r"(u1));                            \
    uint32_t* o = (uint32_t*)(out + eo + (size_t)(s) * 32 * D_);                                         \
    o[0] = add2(mul2(u0, e[0]), e[2]); o[4] = add2(mul2(u1, e[1]), e[3]);                                \
  }
#pragma unroll 1
      for (int s = s0; s < NSEG; s++) {
        float d[16], d2[16];
        int prev = 0;
#pragma unroll
        for (int i = 0; i < 8; i++) {
          mbar_wait(dFull + st * 8, ph);
          const uint32_t db = dB + st * 1024;
          asm volatile("" : "+r"(dA));
          WG_FENCE();
#pragma unroll
          for (int k = 0; k < (DX == 1 ? 2 : 8); k++) {
            if (i < NRD) wgmma_rs32(k & 1 ? d2 : d, W[i < NRD ? i * 8 + k : 0], DSC(db + (k >> 2) * 256 + (k & 3) * 2), (i | (k >> 1)) != 0);
            else wgmma_ss32(k & 1 ? d2 : d, DSC(dA + ((i - NRD) * 8 + k) * 128), DSC(db + (k >> 2) * 256 + (k & 3) * 2), 1);
          }
          WG_COMMIT();
          if (i > 0) { WG_WAIT(1); if (leader) mbar_arrive(dEmpty + prev * 8); }
          if (i == 2) {
            if (s > s0) FINISH(s - 1);
            const size_t o = eo + (size_t)s * 32 * D_;
            e[0] = ld_rlx1(g_gate + o); e[1] = ld_rlx1(g_gate + o + 8);
            e[2] = __ldg((const uint32_t*)(x + o)); e[3] = __ldg((const uint32_t*)(x + o + 8));
            if (leader) mbar_expect_tx(dIn + (wg * 2 + (s & 1)) * 8, 8192);
          }
          prev = st;
          if (++st == D_STAGES) { st = 0; ph ^= 1; }
        }
        WG_WAIT(0);
        asm volatile("" : D16(d));
        asm volatile("" : D16(d2));
        if (leader) mbar_arrive(dEmpty + prev * 8);
#pragma unroll
        for (int j = 0; j < 16; j++) d[j] += d2[j];
#pragma unroll
        for (int j = 0; j < 4; j++) {
          const uint32_t p = j < 2 ? p0 : p1;
          sta4(in + (j & 1) * 16384 + (s & 1) * 8192 + q * 2048 + p, make_uint4(asu(d[4 * j]), asu(d[4 * j + 1]), asu(d[4 * j + 2]), asu(d[4 * j + 3])),
               dIn + ((j & 1) * 2 + (s & 1)) * 8 + p);
        }
        if (tid == 0) TG(24 + s, 1);
      }
      FINISH(NSEG - 1);
    }
    if (tid == 0) { TG(95, 3); ST(32 + cl); }
  }
  asm volatile("barrier.cluster.arrive.relaxed.aligned; barrier.cluster.wait.aligned;" ::: "memory");
}
struct RecMaps { CUtensorMap w[3], wb[3], wo, xn, xn1, xn2, ox; };
#define NR1 13
#define NLOW 5
constexpr int R_WS = 0, R_WO = 2 * (32 - NR1) * 2048, R_Q = R_WO + 81920, R_K = R_Q + 6144, R_G1 = R_K + 6144,
              R_XN = R_WO + 98304, R_MEM = R_XN + 16384, R_VX = R_MEM + 16384, R_VM = R_VX + 8192, R_O = R_VM + 4096,
              R_TS = R_O + 4096, R_SC = R_TS + 5120, R_BAR = R_SC + 1280, R_TAB = R_BAR + 256, R_SMEM = R_TAB + 128;
constexpr int STG = R_SC - 2 * (32 + NR1) * 2048, NDIR = STG / 2048;
__device__ constexpr int stg(int g, int i) { return STG + (i == 0 ? 131072 + g * NR1 * 2048 : (i == 1 ? g * 98304 : 32768 + g * 32768)); }
static_assert(R_SMEM <= 232448 && R_G1 + 2048 <= R_XN && STG % 1024 == 0 && R_WO <= STG + 32768 && R_XN >= STG + 98304, "smem");
constexpr uint32_t SB = 1024;
constexpr int POLL_LIM = 1 << 20;
enum { BAR_MEM = 1, BAR_RED, BAR_O, BAR_BG, BAR_C, BAR_G1, BAR_X, BAR_H, BAR_ST };
#define bC (sb + R_BAR)
#define bX (bC + 48)
#define bWS (bC + 128)
#define bWo (bC + 136)
#define bM (bC + 144)
#define bS (bC + 152)
#define bTs (bC + 176)
#define bIn (bC + 184)
#define bTok (bC + 192)
#define aInfo (bC + 200)
#define aCal (bC + 224)
constexpr int XC_G2N = 256, XC_PRB = 384, XC_T = 386;
#define TINIT 6500, 1100, 200, 300, 400
__constant__ int c_tune[16] = {TINIT};
#define T_STEP c_tune[0]
#define T_G2 c_tune[1]
#define D_G1 c_tune[2]
#define D_G2 c_tune[3]
#define T_REL c_tune[4]
#define NWF 2
#define NBF 2
#define NCH 1
#define PAT 1
#define INSM(k) ((k) % 5 % 2 == 0)
#define SIDX(k) ((k) / 5 * 3 + ((k) % 5 + 1) / 2)
#define RIDX(k) (INSM(k) ? 0 : (k) - SIDX(k))
#define NEA0 3
#define NEA1 3
#define NEB 1
#define HOLE0 6
#define HOLE1 6
#define GST 0
#define THR 0
#define LEAD 15
#define WOT 2
#define WOW 1
#define XPOS 0
#define NPRB 3
#define PFX 2

__device__ __forceinline__ void xn_pair(const CUtensorMap* m, uint32_t dst, uint32_t bar, int bytes, int n, int c, int half) {
  mbar_expect_tx(bar, bytes);
  asm volatile(
      "cp.async.bulk.tensor.4d.shared::cluster.global.mbarrier::complete_tx::bytes [%0], [%1, {%3, %4, %5, %6}], [%2];"
      ::"r"(dst), "l"(m), "r"(bar), "r"(0), "r"(n * 32), "r"(c), "r"(half) : "memory");
}

__global__ void __launch_bounds__(384, 1)
k_rec(const __grid_constant__ RecMaps maps, const bf16* __restrict__ x, const bf16* __restrict__ mem0, unsigned char* xch) {
  extern __shared__ __align__(1024) unsigned char smem_raw[];
  const uint32_t sb = smem_u32(smem_raw);
  if ((sb & 0xffffff) != SB) __trap();
  const int tid = threadIdx.x, wid = __shfl_sync(~0u, tid >> 5, 0), wg = wid >> 2, w = wid & 3;
  const int lane = tid & 31;
  const int cta = blockIdx.x, h = cta / 3, j = cta - h * 3, cl = h >> 1, r0 = (h & 1) * 3;
  const bool isA = j < 2;
  if (tid >= 32 && tid < 32 + 11) asm volatile("prefetch.tensormap [%0];" ::"l"(&maps.w[0] + (tid - 32)) : "memory");
  if (tid == 0 && cta == 0) ST(2);
  asm volatile("griddepcontrol.launch_dependents;" ::: "memory");
  uint32_t u[3][16] = {};
  const int row = min((cta * 8 + wid) * 3, S_ - 3);
  if (wg < 2) {
#pragma unroll
    for (int i = 0; i < 3; i++) row_ld(u[i], x + (size_t)(row + i) * D_, lane);
  }
  if (tid == 0) {
    for (int i = 0; i < 18; i++) mbar_init(bC + i * 8, 1);
    mbar_init(bM, 2); mbar_init(bS, 1); mbar_init(bTs, 1); mbar_init(bIn, 2); mbar_init(bTok, 4);
    asm volatile("fence.mbarrier_init.release.cluster;" ::: "memory");
  }
  if ((wid >> 1) != 4) {
    bar_sync(BAR_G1, 384);
#pragma unroll 1
    for (int pass = wg >> 1; pass < 2; pass++) {
      bf16* dst = (pass ? g_xn2 : g_xn) + (size_t)row * D_;
      if (pass == 0) {
        if (__any_sync(~0u, after(c_tune[15], u[0][15] ^ u[1][15] ^ u[2][15], c_tune[15]))) __trap();
        bar_arrive(BAR_X, 320);
        if (tid == 0) TG(1, 0);
      }
#pragma unroll
      for (int i = 0; i < 3; i++) ln_packed(u[i]);
      if (wg < 2 && (cta * 8 + wid) * 3 < S_) {
#pragma unroll
        for (int i = 0; i < 3; i++) row_st(u[i], dst + i * D_, lane);
      }
    }
  } else {
    bar_arrive(BAR_G1, 384);
    uint4* z = (uint4*)(xch + (isA ? (h * 2 + j) * 4 : XC_G2N + ((h >> 3) & 1) * 48 + (h >> 4) * 64 + ((h >> 1) & 3) * 4 + (h & 1)) * 4096);
#pragma unroll 4
    for (int i = 0; i < (isA ? 16 : 4); i++) z[i * 64 + (tid & 63)] = make_uint4(0, 0, 0, 0);
    if (cta == cl * 6) {
      uint32_t* p = (uint32_t*)(xch + (XC_PRB + w) * 4096 + cl * 128);
      st_rlx1(p + lane, 0);
      uint32_t lat = ~0u;
#pragma unroll 1
      for (int r = 0; r < NPRB && lane == 0; r++) {
        uint32_t v, c0 = clk32();
        asm volatile("atom.relaxed.gpu.global.add.u32 %0, [%1], 1;" : "=r"(v) : "l"(p) : "memory");
        if (v >> 30) break;
        lat = min(lat, clk32() - c0);
      }
      if (lane == 0) { sts_u1(aInfo + w * 4, lat); TG(3, w); }
      __syncwarp();
    }
  }
  asm volatile("barrier.cluster.arrive.relaxed.aligned;" ::: "memory");
#define WMAP(g) (&maps.w[isA ? (g) : 2])
#define WCOL(g) (h * 128 + (isA ? j : (g)) * 64)
  const uint32_t xlo = (uint32_t)(uint64_t)xch, xhi = (uint32_t)((uint64_t)xch >> 32);
#define XP(off) xptr(xlo + (off), xhi)
  if (wg < 2) {
    fence_async_all();
    if (tid == 0) TG(1, 1);
    if (wid != 7) bar_arrive(BAR_C, 256);
    else bar_sync(BAR_C, 256);
    if (tid == 224) { sig_cnt(C_LN); TG(0, 1); }
    __syncwarp();
    if (wid == 7) bar_arrive(BAR_BG, 96);
    asm volatile("setmaxnreg.inc.sync.aligned.u32 224;");
    const uint32_t l16c = opaque(sb + lane * 16);
    const uint32_t xwc = opaque(sb + ((lane >> 4) * 8 + (lane & 7)) * 128 + (((w * 2 + ((lane >> 3) & 1)) ^ (lane & 7)) << 4));
    uint32_t W0[32][4], W1[NR1][4];
#pragma unroll
    for (int i = 0; i < 3; i++) {
      mbar_wait(bC + (wg * 3 + i) * 8, 0);
      if (i == 0 && tid == 0) TG(1, 2);
#pragma unroll
      for (int k = 0; k < (i ? 16 : NR1); k++) ldsm4t(i ? W0[i ? i * 16 - 16 + k : 0] : W1[i ? 0 : k], (wg ? stg(1, i) : stg(0, i)) + k * 2048 + xwc);
      if (i) bar_arrive(i == 1 ? BAR_ST : BAR_H, 288);
    }
    if (tid == 0) TG(1, 3);
    asm volatile("barrier.cluster.wait.aligned;" ::: "memory");
    mbar_wait(bWS, 0);
    if (tid == 0) TG(0, 2);
    const uint32_t dX = (uint32_t)make_desc(SB + R_XN, 16, 1024, 1) + wg * 512, dW = (uint32_t)make_desc(SB + R_WS, 1024, 1024, 1) + wg * (32 - NR1) * 128;
    const uint32_t pB = peer_base(sb, r0 + 2);
#pragma unroll 1
    for (int s = 0; s < NSEG; s++) {
      uint32_t xw = xwc, l16 = l16c;
      asm volatile("" : "+r"(xw), "+r"(l16));
#define LANE0 ((l16 & 511) == 0)
      {
        float d0[16], d1[16];
#pragma unroll
        for (int c = 0; c < 8; c++) {
          if (c == 7 || !(c & 1)) mbar_wait(bX + (c < 4 ? c / 2 : (c == 7 ? 6 : c - 2) + wg) * 8, s & 1);
          if (c <= 3 && s > 0 && c == (isA ? (wg ? NEA1 : NEA0) : NEB)) bar_sync(BAR_BG, 384);
          if ((c == HOLE0 || c == HOLE1) && s > 0 && isA && c == (wg ? HOLE1 : HOLE0)) bar_sync(BAR_H, 384);
          const uint32_t db = dX + (c & 2) * 512 + (c & 1) * 256 + (c < 4 ? 0 : c_tune[15]);
          uint32_t tmp[4];
          if (c < NLOW) {
#pragma unroll
            for (int i = 0; i < 4; i++) asm volatile("or.b32 %0, %1, %2;" : "=r"(tmp[i]) : "r"(W0[c * 4][i]), "r"(c_tune[15]));
          }
          WG_FENCE();
#pragma unroll
          for (int kk = 0; kk < 4; kk++) {
            const int k = c * 4 + kk;
            if (c < 7) wgmma_rs32(d0, kk == 0 && c < NLOW ? tmp : W0[k], DSC(db + kk * 2), k != 0);
            if (kk == 0 && c + 1 < NLOW) WG_COMMIT();
            if (!INSM(k)) wgmma_rs32(d1, W1[RIDX(k)], DSC(db + kk * 2), k != 0);
            else wgmma_ss32(d1, DSC(dW + SIDX(k) * 128), DSC(db + kk * 2), k != 0);
          }
          WG_COMMIT();
          if (c == 7) {
#pragma unroll
            for (int kk = 0; kk < 4; kk++) wgmma_rs32(d0, W0[28 + kk], DSC(db + kk * 2), 1);
            WG_COMMIT();
          }
          const bool pause = c + 1 == (isA ? (wg ? NEA1 : NEA0) : NEB);
          if ((c == 1 || c == 2) && pause) WG_WAIT(0);
          if (c + 1 < NLOW || c == 4) WG_WAIT(1);
#pragma unroll
          for (int f = 1; f <= 3; f++) {
            if (f != c && f + 1 != c) continue;
            const bool early = f < 3 && f + 1 == (isA ? (wg ? NEA1 : NEA0) : NEB);
            if (w == 0 && LANE0 && early == (f == c)) {
              if (f == 1) {
                xn_pair(&maps.xn1, sb + R_XN + wg * 8192, bX + (2 + wg) * 8, 8192, s, 4, wg);
              } else {
                mbar_expect_tx(bX + (f * 2 + wg) * 8, 4096);
                tma_load_2d(sb + R_MEM + wg * 8192 + (f - 2) * 4096, &maps.xn, wg * 512 + (f + 4) * 64, s * 32, bX + (f * 2 + wg) * 8);
              }
            }
            __syncwarp();
          }
        }
        const uint32_t ex = l16 + R_XN + w * 2048;
        WG_WAIT(1);
        asm volatile("" : D16(d1));
#pragma unroll
        for (int i = 0; i < 4; i++) sts_f4(ex + wg * 8192 + i * 512, d1 + 4 * i);
        bar_sync(BAR_C, 256);
#pragma unroll
        for (int i = 0; i < 4; i++) {
          const float4 x = lds_f4(ex + (wg ^ 1) * 8192 + i * 512);
          d1[4 * i] = x.x; d1[4 * i + 1] = x.y; d1[4 * i + 2] = x.z; d1[4 * i + 3] = x.w;
        }
        WG_WAIT(0);
        asm volatile("" : D16(d0));
        if (w == 0 && LANE0) mbar_arrive(bM);
        if (s > 0 && tid < 32) { s--; TR(17); s++; }
        uint32_t f[8];
#pragma unroll
        for (int i = 0; i < 8; i++) f[i] = pack_bf16(d0[2 * i] + d1[2 * i], d0[2 * i + 1] + d1[2 * i + 1]);
        if (isA) {
          const uint32_t aq = l16 + (l16 & 256) * 3 + R_Q + wg * 6144 + w * 256;
          stsm4t(aq, f[0], f[1], f[2], f[3]);
          stsm4t(aq + 2048, f[4], f[5], f[6], f[7]);
        } else {
          const uint32_t av = l16 + R_VX + w * 2048 + wg * 1024;
          if (s > 0) mbar_wait(bTok, (s - 1) & 1);
          sts_u4(av, make_uint4(f[0], f[1], f[2], f[3])); sts_u4(av + 512, make_uint4(f[4], f[5], f[6], f[7]));
        }
        if (s > 0 && tid < 32) { s--; TR(18); s++; }
      }
      {
        const uint32_t aW = xw + R_WS + wg * (32 - NR1) * 2048, aMem = l16 + R_MEM + wg * 8192;
        float a[4][4];
        uint32_t b[16][4], f[32 - NR1][4], ck[14];
#define PAIR(i) (i)
#pragma unroll
        for (int i = 0; i < NWF; i++) ldsm4t(f[i], aW + i * 2048);
#pragma unroll
        for (int i = 0; i < 4; i++) a[i][0] = a[i][1] = a[i][2] = a[i][3] = 0.f;
        bar_sync(BAR_MEM, 384);
#pragma unroll
        for (int i = 0; i < NBF - 1; i++) ldsm4t(b[i], aMem + PAIR(i) * 512);
#pragma unroll
        for (int i = 0; i < 16; i++) {
          const int p = PAIR(i);
          if (i + NBF - 1 < 16) ldsm4t(b[i + NBF - 1], aMem + PAIR(i + NBF - 1) * 512);
#pragma unroll
          for (int e = 0; e < 2; e++) {
            const int k = 2 * PAIR(i > 0 ? i - 1 : 0) + e, q = SIDX(k) + NWF;
            if (i > 0 && INSM(k) && q < 32 - NR1) ldsm4t(f[q], aW + q * 2048);
          }
          if (i < 14) ck[i] = clk32();
          if (i == 1 && tid < 32) TRX(0, ck[0]);
          if (i > 1) ck[0] |= ck[i - 2];
#pragma unroll
          for (int e = 0; e < 2; e++) {
            const int k = 2 * p + e;
            const uint32_t* u = INSM(k) ? f[INSM(k) ? SIDX(k) : 0] : W1[RIDX(k)];
            mma16816(a[2 + e % NCH], u[0], u[1], u[2], u[3], b[i][2 * e], b[i][2 * e + 1]);
            mma16816(a[e % NCH], W0[k][0], W0[k][1], W0[k][2], W0[k][3], b[i][2 * e], b[i][2 * e + 1]);
          }
        }
        l16 = after(l16, ck[0], 0);
        if (NCH == 2) {
#pragma unroll
          for (int i = 0; i < 4; i++) { a[0][i] += a[1][i]; a[2][i] += a[3][i]; }
        }
        const uint4 r = make_uint4(pack_bf16(a[0][0], a[0][1]), pack_bf16(a[0][2], a[0][3]), pack_bf16(a[2][0], a[2][1]), pack_bf16(a[2][2], a[2][3]));
        if (!isA) {
          sts_u4(l16 + R_VM + wid * 512, r);
          bar_arrive(BAR_RED, 384);
          if (tid < 32) TR(1);
          if (tid == 160) TRCAL(s);
          __syncwarp();
          continue;
        }
        stsm4t((l16 & ~256u) + (((l16 >> 8) & 1) ^ wg) * 6144 + R_Q + 4096 + wg * 1024 + w * 256, r.x, r.y, r.z, r.w);
        bar_arrive(BAR_RED, 384);
        fence_async_smem();
        bar_sync(BAR_X, 352);
        if (tid < 32) TR(1);
        if (tid == 160) TRCAL(s);
        __syncwarp();
      }
      if (wg == 0) {
        float c[24];
        WG_FENCE();
#pragma unroll
        for (int i = 0; i < 4; i++) wgmma_ss48(c, make_desc(SB + R_Q + i * 256, 128, 1024, 0), make_desc(SB + R_K + i * 256, 128, 1024, 0), i != 0);
        WG_COMMIT();
        asm volatile("" : "+r"(l16));
        const uint32_t at = l16 + R_TS + w * 2560 + j * 640 + pB, au = at + 512 - (l16 & 511) / 4 * 3;
        mbar_wait(bIn, s & 1);
        WG_WAIT(0);
        asm volatile("" : D16(c), "+f"(c[16]), "+f"(c[17]), "+f"(c[18]), "+f"(c[19]), "+f"(c[20]), "+f"(c[21]), "+f"(c[22]), "+f"(c[23]));
        if (w < 2) {
#pragma unroll
          for (int r = 0; r < 2; r++) {
            const float* e = c + 2 * r;
            sta4(at + r * 1280, make_uint4(pack_bf16(e[0], e[1]), pack_bf16(e[4], e[5]), pack_bf16(e[8], e[9]), pack_bf16(e[12], e[13])), bTs + pB);
            sta1(au + r * 1280, pack_bf16(e[16] + e[20], e[17] + e[21]), bTs + pB);
          }
        }
        if (tid < 32) TR(14);
      }
    }
  } else {
    asm volatile("setmaxnreg.dec.sync.aligned.u32 56;");
    const int at = tid & 127, red = h * 2 + j;
    const int g = w & 1, slot = g * (32 - NR1) + SIDX(lane);
    if (w >= 2) {
      const bool lead = cl == LEAD;
      if (lead) bar_arrive(BAR_X, 320);
      else bar_sync(BAR_X, 320);
      if (lane < 3) mbar_expect_tx(bC + (g * 3 + lane) * 8, lane ? 32768 : NR1 * 2048);
      if (lane == 3 && g) mbar_expect_tx(bWS, R_WO);
      if (!INSM(lane)) tma_load_2d_ef(sb + stg(0, 0) + (g * NR1 + RIDX(lane)) * 2048, WMAP(g ^ 1), WCOL(g ^ 1), g * 512 + lane * 16, bC + g * 24);
      __syncwarp();
#pragma unroll 1
      for (int i = 0; i < 3; i++) {
        if (i == (lead ? 2 : XPOS)) bar_sync(BAR_BG, 96);
        if (i >= THR && !lead) mbar_wait(bC + (g * 3 + i - THR) * 8, 0);
        if (lane == 0 && i < 2) tma_load_2d_ef(sb + STG + (i ? g + 1 : g * 3) * 32768, WMAP(g) + 3, WCOL(g), g * 512 + i * 256, bC + (g * 3 + 1 + i) * 8);
        __syncwarp();
      }
      if (INSM(lane) && slot < NDIR) tma_load_2d_ef(sb + R_WS + slot * 2048, WMAP(g ^ 1), WCOL(g ^ 1), g * 512 + lane * 16, bWS);
      __syncwarp();
    }
    if (w == 3) {
      bar_sync(BAR_ST, 288);
      fence_async_smem();
      if (INSM(lane) && slot >= NDIR) tma_load_2d_ef(sb + R_WS + slot * 2048, WMAP(0), WCOL(0), 512 + lane * 16, bWS);
      __syncwarp();
      if (lane < 2) {
        wait_cnt(C_LN, gridDim.x);
        fence_async_all();
        xn_pair(&maps.xn2, sb + R_XN + lane * 16384, bX + lane * 8, 16384, 0, lane * 2, 0);
        TG(2, 1);
      }
      __syncwarp();
    }
    if (w < 2) bar_sync(BAR_RED, 64);
    if (at == 0) {
      uint32_t v = 1;
      if (cta == cl * 6) v += ((__popc((XC_PRB + (lds_u1(aInfo + 4) < lds_u1(aInfo))) & 0xb3) & 1) << cl) << 16;
      asm volatile("red.release.gpu.global.add.u32 [%0], %1;" ::"l"(g_cnt + C_CHK * 8), "r"(v) : "memory");
      int n = 0;
#pragma unroll 1
      do {
        asm volatile("ld.acquire.gpu.global.u32 %0, [%1];" : "=r"(v) : "l"(g_cnt + C_CHK * 8) : "memory");
      } while ((v & 0xffff) < gridDim.x && ++n < WAIT_LIM);
      sts_u1(aInfo + 8, v >> 16);
      TG(2, 0);
    }
    bar_sync(BAR_O, 128);
    const uint32_t pmask = __shfl_sync(~0u, lds_u1(aInfo + 8), 0), myp = (pmask >> cl) & 1;
    const int nt = isA ? 5 : 6;
    uint32_t mytile = 0;
    {
      int n = 0;
      for (int far = 1; far >= 0; far--)
        for (int i = 0; i < nt; i++) {
          const int T = j * 5 + i, p = (pmask >> T) & 1;
          if ((p ^ myp) != far) continue;
          if (n == lane) {
            mytile = T;
            sts_u1(sb + R_TAB + w * 32 + n * 4, xlo + xchunk((T * 4 + w) * 4 + (h >> 4) * 2, p) + (h & 15) * 256);
          }
          n++;
        }
    }
    if (w == 3) {
      bar_sync(BAR_H, 288);
      fence_async_smem();
      if (WOW) mbar_wait(bWS, 0);
#pragma unroll 1
      for (int i = 0; i < nt; i++) {
        if (i >= WOT) mbar_wait(bC + (i - WOT) * 8, 1);
        const bool tail = i >= nt - WOT;
        if (lane == i) {
          if (!tail || i == nt - 1) mbar_expect_tx(tail ? bWo : bC + i * 8, tail ? WOT * 16384 : 16384);
          tma_load_2d(sb + R_WO + i * 16384, &maps.wo, mytile * 64, h * 128, tail ? bWo : bC + i * 8);
        }
        __syncwarp();
      }
    }
    asm volatile("barrier.cluster.wait.aligned;" ::: "memory");
    {
      uint4 v[8];
#pragma unroll
      for (int i = 0; i < 8; i++) v[i] = __ldg((const uint4*)(mem0 + (lane >> 2) * D_ + w * 256 + i * 32 + (lane & 3) * 8));
      mbar_wait(bM, 0);
#pragma unroll
      for (int i = 0; i < 8; i++)
        stsm4t(sb + R_MEM + w * 4096 + i * 512 + (lane & 6) * 64 + (lane >> 3) * 32 + (lane & 1) * 16, v[i].x, v[i].y, v[i].z, v[i].w);
    }
    if (at == 96) { const uint2 e = timer_edge(); sts_u2(aCal, e.x, e.y); }
    int lim = POLL_LIM;
    const uint32_t l8c = opaque(lane * 8);
    const uint32_t pA = peer_base(sb, r0), pB = peer_base(sb, r0 + 2 - (j >> 1));
    const uint32_t uR = xchunk(red * 4 + (w & 2), myp) + (w & 1) * 2048;
    const uint32_t uW = xchunk(XC_G2N + (red >> 4) * 4, (myp ^ w ^ 1) & 1) + (red & 15) * 256;
    const uint32_t uG = xchunk(XC_G2N, myp) + w * 512;
    const uint64_t dWo = make_desc(SB + R_WO, 1024, 1024, 1), dO = make_desc(SB + R_O, 128, 128, 0);
#pragma unroll 1
    for (int s = 0; s < NSEG; s++) {
      const uint32_t tag = (s & 1) ^ 1, par = s & 1;
      const bool more = s + 1 < NSEG;
      uint32_t l8 = l8c;
      asm volatile("" : "+r"(l8));
#define STORE_OX(n, w) do {                                                                 \
          tma_store_2d(&maps.ox, sb + R_O + (w) * 1024, h * 128 + (w) * 16, (n) * 32);         \
          tma_store_2d(&maps.ox, sb + R_TS + (w) * 1280, h * 128 + 64 + (w) * 16, (n) * 32); } while (0)
      bar_sync(BAR_MEM, 384);
      if (w == 3) {
        if (l8 == 0) {
          const uint32_t ta = ld_rlx1(XP(XC_T << 12));
          if (more) {
            fence_async_smem();
            xn_pair(&maps.xn2, sb + R_XN, bX, 16384, s + 1, 0, 0);
            mbar_expect_tx(bS, isA ? 2048 : 1280);
          }
          if (!isA) mbar_expect_tx(bTs, 5120);
          const uint4 o = lds_u4(aCal);
          const uint2 e = timer_edge();
          float f = (float)(e.y - o.y) * rcp((float)(e.x - o.x));
          if (s > 1) f = 0.75f * asf(o.z) + 0.25f * f;
          uint32_t d = (int)((float)(int)(ta - e.x) * f);
          if (d > 8192) d = 0;
          sts_u4(aCal, make_uint4(e.x, e.y, asu(f), ta));
#pragma unroll
          for (int i = 0; i < 4; i++) sts_u1(sb + R_TAB + i * 32 + 24, e.y + d);
        }
        if (s + PFX < NSEG && l8 < 128)
          asm volatile("prefetch.global.L2 [%0];" ::"l"(g_xn + (size_t)(s + PFX) * 32 * D_ + (cta & 31) * 1024 + l8 * 8));
      }
#define XN23() do { if (w == 3 && l8 == 0 && more) { fence_async_smem(); xn_pair(&maps.xn2, sb + R_MEM, bX + 8, 16384, s + 1, 2, 0); } __syncwarp(); } while (0)
      if (s == 0 && at == 0) TG(2, 3);
      if (s == 0) mbar_wait(bWo, 0);
      if (s == 0 && at == 0) TG(2, 2);
      if (isA && more && w < 3) {
        uint32_t k[4][4], q[4][4];
        uint32_t ak = sb + R_K + w * 2048 + l8 * 2 + (l8 & 128) * 6, aq = sb + R_Q + 4096 + (l8 & 63) * 2 + (l8 & 64) * 16 + (l8 & 128);
        asm volatile("" : "+r"(ak), "+r"(aq));
        if (w == 2) bar_sync(BAR_RED, 384);
#pragma unroll
        for (int i = 0; i < 4; i++) ldsm4(k[i], ak + i * 256);
        if (w != 2) bar_sync(BAR_RED, 384);
#pragma unroll
        for (int i = 0; i < 4; i++) ldsm4(q[i], aq + i * 256);
        float c[4][4];
#pragma unroll
        for (int i = 0; i < 4; i++) c[i][0] = c[i][1] = c[i][2] = c[i][3] = 0.f;
#pragma unroll
        for (int i = 0; i < 4; i++) {
          mma16816(c[i & 1], q[i][0], q[i][1], q[i][2], q[i][3], k[i][0], k[i][1]);
          mma16816(c[2 + (i & 1)], q[i][0], q[i][1], q[i][2], q[i][3], k[i][2], k[i][3]);
        }
        const float a0 = (c[0][0] + c[0][2]) + (c[1][0] + c[1][2]), a1 = (c[0][1] + c[0][3]) + (c[1][1] + c[1][3]);
        const float b0 = (c[2][0] + c[2][2]) + (c[3][0] + c[3][2]), b1 = (c[2][1] + c[2][3]) + (c[3][1] + c[3][3]);
        const uint32_t as = sb + R_SC + j * 640 + w * 256;
        if (w < 2) {
          const uint32_t x = pack_bf16(a0, a1), y = pack_bf16(b0, b1);
          sta2(as + l8 + pB, x, y, bS + pB);
        } else {
          const uint32_t x = pack_bf16(a0 + b0, a1 + b1);
          sta1(as + (l8 >> 1) + pB, x, bS + pB);
        }
        bar_arrive(BAR_X, 352);
        if (w == 0) TR(2);
      } else if (isA) {
        bar_sync(BAR_RED, 384);
        if (w < 3) bar_arrive(BAR_X, 352);
        XN23();
      } else {
        if (w < 2 && l8 == 0) {
          if (s > 0) {
            fence_async_smem();
            STORE_OX(s - 1, 2 * w); STORE_OX(s - 1, 2 * w + 1);
            asm volatile("cp.async.bulk.commit_group; cp.async.bulk.wait_group 1; cp.async.bulk.wait_group.read 0;" ::: "memory");
          }
          arrive_remote(bIn + pA); arrive_remote(bIn + pB);
          if (s > 1) sig_cnt(C_OX + s - 2, 2);
          if (!more) { asm volatile("cp.async.bulk.wait_group 0;" ::: "memory"); sig_cnt(C_OX + s - 1, 2); }
        }
        __syncwarp();
        uint4 vx[4];
#pragma unroll
        for (int i = 0; i < 4; i++) vx[i] = lds_u4(sb + R_VX + (i & 1) * 1024 + (i >> 1) * 512 + w * 2048 + l8 * 2);
        bar_sync(BAR_RED, 384);
        XN23();
        if (more) {
          const uint32_t am = sb + R_VM + w * 512 + l8 * 2;
          const uint2 vm[4] = {lds_u2(am), lds_u2(am + 2056), lds_u2(am + 8), lds_u2(am + 2048)};
          mbar_wait(bS, par);
          if (w == 0) TR(4);
          float sc[10];
          const uint2 u0 = lds_u2(sb + R_SC + l8), u1 = lds_u2(sb + R_SC + 256 + l8), v0 = lds_u2(sb + R_SC + 640 + l8), v1 = lds_u2(sb + R_SC + 896 + l8);
          sum_scores(sc, u0, u1, lds_u1(sb + R_SC + 512 + (l8 >> 1)), v0, v1, lds_u1(sb + R_SC + 1152 + (l8 >> 1)));
          uint32_t p[5];
          softmax_e(sc);
#pragma unroll
          for (int i = 0; i < 5; i++) p[i] = pack_bf16(sc[2 * i], sc[2 * i + 1]);
          if (w == 0) TR(5);
          float o0[4], o1[4], sm[4];
          pv_mma(o0, o1, sm, vx, vm, p);
          const float i0 = rcp(sm[0]), i1 = rcp(sm[1]);
          const uint32_t aO = sb + R_O + w * 512 + (l8 >> 1);
          const uint32_t o[4] = {pack_bf16(o0[0] * i0, o0[1] * i1), pack_bf16(o0[2] * i0, o0[3] * i1), pack_bf16(o1[0] * i0, o1[1] * i1), pack_bf16(o1[2] * i0, o1[3] * i1)};
#pragma unroll
          for (int i = 0; i < 4; i++) { sta1(aO + i * 128 + pA, o[i], bS + pA); sta1(aO + i * 128 + pB, o[i], bS + pB); }
#pragma unroll
          for (int i = 0; i < 4; i++) sts_u1(aO + i * 128, o[i]);
        }
      }
      if (!more && isA) break;
      const uint32_t ts = sb + R_TS + w * 1280;
      uint4 tu, tv;
      uint32_t tu4, tv4, tp = 0;
#define LOAD_TS() tu = lds_u4(ts + l8 * 2); tv = lds_u4(ts + 640 + l8 * 2); tu4 = lds_u1(ts + 512 + (l8 >> 1)); tv4 = lds_u1(ts + 1152 + (l8 >> 1))
      if (!more) {
        mbar_wait(bTs, par);
        LOAD_TS();
      } else {
        float m[6][4];
        const uint4 ta = lds_u4(sb + R_TAB + w * 32);
        const uint4 tb = lds_u4(sb + R_TAB + w * 32 + 16);
        tp = tb.z;
        if (isA) mbar_wait(bS, par);
        else bar_sync(BAR_O, 128);
        fence_async_smem();
        if (w == 0) TR(8);
        WG_FENCE();
#define WO_GROUP(t0, t1)                                                                                          \
  _Pragma("unroll") for (int kk = 0; kk < 8; kk++) _Pragma("unroll") for (int i = t0; i < t1; i++)                \
      wgmma_n8_tt(m[i], dWo + i * 1024 + kk * 128, dO + (kk & 3) * 32 + (kk >> 2) * 16, kk != 0);                 \
  WG_COMMIT();
        WO_GROUP(0, 3)
        if (isA) { wgmma_n8_tt(m[5], dWo, dO, 0); WO_GROUP(3, 5) } else { WO_GROUP(3, 6) }
#define G1_SEND(i, lo) st_rlx2(xptr(lo + l8, xhi), tagu(pack_bf16(m[i][0], m[i][1]), tag), pack_bf16(m[i][2], m[i][3]))
#define PIN4(i) asm volatile("" : "+f"(m[i][0]), "+f"(m[i][1]), "+f"(m[i][2]), "+f"(m[i][3]))
        WG_WAIT(1);
        PIN4(0); PIN4(1); PIN4(2);
        G1_SEND(0, ta.x); G1_SEND(1, ta.y); G1_SEND(2, ta.z);
        mbar_wait(isA ? bS : bTs, par);
        LOAD_TS();
        WG_WAIT(0);
        PIN4(3); PIN4(4); PIN4(5);
        bar_arrive(BAR_BG, 384);
        G1_SEND(3, ta.w); G1_SEND(4, tb.x);
        if (!isA) G1_SEND(5, tb.y);
        if (w == 0) TR(9);
      }
      const uint32_t slot = ((s & 1) * 48 + (s & 2) * 32) << 12;
      asm volatile("" : "+r"(l8));
      if (isA) {
        const unsigned char* pR = XP(uR + l8);
        unsigned char* pW = XP(((uW + slot) ^ ((w & 2) << 17)) + l8);
        uint32_t sel = (l8 >> 6) == ((l8 >> 3) & 3) ? (l8 & 32 ? 0x3F800000u : 0x3F80u) : 0;
        asm volatile("" : "+r"(sel), "+l"(pR), "+l"(pW));
        uint32_t ci = wait_clk(tp, D_G1), bad;
        if (w == 0) TRX(10, ci);
#pragma unroll 1
        do {
          uint2 p[8];
#pragma unroll
          for (int i = 0; i < 8; i++) p[i] = ld_rlx2(pR + i * 256);
          ci = clk32();
          float d[2][4] = {};
#pragma unroll
          for (int i = 0; i < 4; i++) mma16816(d[i & 1], p[2 * i].x, p[2 * i].y, p[2 * i + 1].x, p[2 * i + 1].y, sel, sel);
          bad = or3(ne2(p[0].x, p[1].x, tag), ne2(p[2].x, p[3].x, tag), ne2(p[4].x, p[5].x, tag)) | ne2(p[6].x, p[7].x, tag);
          sts_u2(sb + R_G1 + w * 512 + l8, asu(d[0][0] + d[1][0]), asu(d[0][1] + d[1][1]));
          sts_u2(sb + R_G1 + w * 512 + 256 + l8, asu(d[0][2] + d[1][2]), asu(d[0][3] + d[1][3]));
        } while (__any_sync(~0u, (bad & 1) && --lim > 0));
        bar_sync(BAR_G1, 128);
        if (w < 2) {
          const float4 a = lds_f4(sb + R_G1 + l8 * 2), b = lds_f4(sb + R_G1 + 512 + l8 * 2), c = lds_f4(sb + R_G1 + 1024 + l8 * 2), d = lds_f4(sb + R_G1 + 1536 + l8 * 2);
          st_rlx2(pW, nz(pack_bf16((a.x + b.x) + (c.x + d.x), (a.y + b.y) + (c.y + d.y))),
                  nz(pack_bf16((a.z + b.z) + (c.z + d.z), (a.w + b.w) + (c.w + d.w))));
        } else {
          st_rlx2(pW, 0, 0);
        }
        bar_arrive(BAR_H, 384);
        if (w == 0) TR(12);
        if (w == 0) TRX(11, ci);
        if (cta == 0 && w == 3) {
          const uint4 o = lds_u4(aCal);
          const bool late = (int)(ci - tp) > 200;
          st_rlx1(XP(XC_T << 12), (late ? o.x : o.w) + (int)((float)(int)(T_STEP + (late ? ci - o.y + T_REL : 0)) * rcp(asf(o.z))));
        }
      } else {
        const uint32_t av = sb + R_VX + w * 2048 + l8 * 2, am = sb + R_VM + w * 512 + l8 * 2;
        float sc[10];
        sum_scores(sc, make_uint2(tu.x, tu.y), make_uint2(tu.z, tu.w), tu4, make_uint2(tv.x, tv.y), make_uint2(tv.z, tv.w), tv4);
        uint4 x = lds_u4(av), y = lds_u4(av + 512);
        uint2 m0 = lds_u2(am), m1 = lds_u2(am + 2056);
        const int lim_k = w * 8 + (l8 >> 5) - ((l8 >> 2) & 6);
#pragma unroll
        for (int i = 0; i < 8; i++)
          if ((i >> 1) * 8 + (i & 1) > lim_k) sc[i] = -1.0e9f * 11.313708498984761f;
        softmax_e(sc);
        float sum = ((sc[0] + sc[1]) + (sc[2] + sc[3])) + ((sc[4] + sc[5]) + (sc[6] + sc[7])) + (sc[8] + sc[9]);
        sum += __shfl_xor_sync(~0u, sum, 1);
        sum += __shfl_xor_sync(~0u, sum, 2);
        const float inv = rcp(sum);
#pragma unroll
        for (int i = 0; i < 6; i++) sts_u1(ts + i * 128 + (l8 >> 1), pack_bf16(sc[i < 5 ? 2 * i : 8] * inv, sc[i < 5 ? 2 * i + 1 : 9] * inv));
        fence_async_smem();
        bar_sync(BAR_O, 128);
        const uint32_t ao = sb + (l8 & 128) * 2 + (l8 & 56) * 4 + (((l8 >> 2) ^ (l8 >> 1)) & 16);
#pragma unroll
        for (int t = 0; t < 2; t++) {
          const uint32_t a0[4] = {x.x, x.y, x.z, x.w}, a1[4] = {y.x, y.y, y.z, y.w}, a2[4] = {m0.x, m0.y, m1.x, m1.y};
          float d[16];
          WG_FENCE();
          wgmma_rs32(d, a0, make_desc(SB + R_TS, 128, 1280, 0), 0);
          wgmma_rs32(d, a1, make_desc(SB + R_TS + 256, 128, 1280, 0), 1);
          wgmma_rs32(d, a2, make_desc(SB + R_TS + 512, 128, 1280, 0), 1);
          WG_COMMIT();
          if (t == 0) { x = lds_u4(av + 1024); y = lds_u4(av + 1536); m0 = lds_u2(am + 8); m1 = lds_u2(am + 2048); }
          WG_WAIT(0);
          asm volatile("" : D16(d));
          if (t == 0) {
#define CPY(v) asm volatile("or.b32 %0, %0, %1;" : "+r"(v) : "r"(c_tune[15]))
            CPY(x.x); CPY(x.y); CPY(x.z); CPY(x.w); CPY(y.x); CPY(y.y); CPY(y.z); CPY(y.w); CPY(m0.x); CPY(m0.y); CPY(m1.x); CPY(m1.y);
            __syncwarp();
            if (l8 == 0) mbar_arrive(bTok);
          }
          stsm4t(ao + (t ? R_TS + w * 1280 : R_O + w * 1024), pack_bf16(d[0], d[1]), pack_bf16(d[2], d[3]), pack_bf16(d[4], d[5]), pack_bf16(d[6], d[7]));
          stsm4t(ao + (t ? R_TS + w * 1280 : R_O + w * 1024) + 512, pack_bf16(d[8], d[9]), pack_bf16(d[10], d[11]), pack_bf16(d[12], d[13]), pack_bf16(d[14], d[15]));
        }
        if (w == 0) TR(13);
        if (!more) {
          fence_async_smem();
          __syncwarp();
          if (l8 == 0) {
            STORE_OX(s, w);
            asm volatile("cp.async.bulk.commit_group; cp.async.bulk.wait_group 0;" ::: "memory");
            sig_cnt(C_OX + s);
            if (w == 0) TG(0, 3);
            if (cta == 2) ST(4);
          }
          break;
        }
      }
      {
        const unsigned char* src = XP(uG + slot + l8 * 2);
        const uint32_t dst = sb + R_MEM + w * 512 + l8 * 2;
        wait_clk(tp + T_G2, isA ? D_G2 : 0);
        if (w == 0) TR(16);
        uint4 p[8];
#pragma unroll
        for (int i = 0; i < 8; i++) p[i] = ld_rlx4(src + (i >> 1) * 16384 + (i & 1) * 2048);
        mbar_wait(bM, par ^ 1);
        uint32_t mn = ~0u, ck = 0;
#pragma unroll
        for (int i = 0; i < 8; i += 2) {
          mn = __vimin3_u32(mn, p[i].x, p[i + 1].x);
          asm volatile("" : "+r"(mn));
          sts_u4(dst + i * 2048, p[i]);
          sts_u4(dst + i * 2048 + 2048, p[i + 1]);
          mn = __vimin3_u32(mn, __vimin3_u32(p[i].y, p[i].z, p[i].w), __vimin3_u32(p[i + 1].y, p[i + 1].z, p[i + 1].w));
          asm volatile("" : "+r"(mn));
        }
        if (__builtin_expect(__any_sync(~0u, mn == 0u), 0)) {
#pragma unroll 1
          do {
#pragma unroll
            for (int i = 0; i < 8; i++) reld4(p[i], src + (i >> 1) * 16384 + (i & 1) * 2048, min4(p[i]));
            mn = ~0u;
#pragma unroll
            for (int i = 0; i < 8; i++) { sts_u4(dst + i * 2048, p[i]); mn = min(mn, min4(p[i])); }
          } while (__any_sync(~0u, mn == 0u && --lim > 0));
          lim = after(lim, ck, 0);
        }
        if (w == 0) TR(15);
      }
    }
  }
  asm volatile("barrier.cluster.arrive.relaxed.aligned; barrier.cluster.wait.aligned;" ::: "memory");
}

typedef CUresult (*EncodeFn)(CUtensorMap*, CUtensorMapDataType, cuuint32_t, void*, const cuuint64_t*, const cuuint64_t*,
                             const cuuint32_t*, const cuuint32_t*, CUtensorMapInterleave, CUtensorMapSwizzle,
                             CUtensorMapL2promotion, CUtensorMapFloatOOBfill);
static EncodeFn g_encode = nullptr;

#define PROMO CU_TENSOR_MAP_L2_PROMOTION_L2_256B
static void map2d(CUtensorMap* m, const void* p, uint64_t cols, uint64_t rows, uint32_t bc, uint32_t br,
                  CUtensorMapSwizzle sw) {
  cuuint64_t dims[2] = {cols, rows}, strides[1] = {cols * 2};
  cuuint32_t box[2] = {bc, br}, es[2] = {1, 1};
  g_encode(m, CU_TENSOR_MAP_DATA_TYPE_BFLOAT16, 2, (void*)p, dims, strides, box, es, CU_TENSOR_MAP_INTERLEAVE_NONE, sw,
           sw == CU_TENSOR_MAP_SWIZZLE_64B ? PROMO : CU_TENSOR_MAP_L2_PROMOTION_L2_256B, CU_TENSOR_MAP_FLOAT_OOB_FILL_NONE);
}
static void map_w(CUtensorMap* m, const void* p, uint64_t N, uint64_t K) {
  cuuint64_t dims[3] = {64, K, N / 64}, strides[2] = {N * 2, 128};
  cuuint32_t box[3] = {64, 64, 2}, es[3] = {1, 1, 1};
  g_encode(m, CU_TENSOR_MAP_DATA_TYPE_BFLOAT16, 3, (void*)p, dims, strides, box, es, CU_TENSOR_MAP_INTERLEAVE_NONE,
           CU_TENSOR_MAP_SWIZZLE_128B, CU_TENSOR_MAP_L2_PROMOTION_L2_256B, CU_TENSOR_MAP_FLOAT_OOB_FILL_NONE);
}
static void map_seg(CUtensorMap* m, const void* p, uint64_t K, uint64_t parts, uint32_t np, CUtensorMapL2promotion pr = CU_TENSOR_MAP_L2_PROMOTION_L2_256B) {
  cuuint64_t dims[4] = {64, S_, K / 64 / parts, parts}, strides[3] = {K * 2, 128, K * 2 / parts};
  cuuint32_t box[4] = {64, 32, 2, np}, es[4] = {1, 1, 1, 1};
  g_encode(m, CU_TENSOR_MAP_DATA_TYPE_BFLOAT16, 4, (void*)p, dims, strides, box, es, CU_TENSOR_MAP_INTERLEAVE_NONE,
           CU_TENSOR_MAP_SWIZZLE_128B, pr, CU_TENSOR_MAP_FLOAT_OOB_FILL_NONE);
}
template <typename T>
static void* sym(T& s) { void* p = nullptr; cudaGetSymbolAddress(&p, s); return p; }

static void map_a(CUtensorMap* m, const void* p, int K) { map2d(m, p, K, S_, 64, 128, CU_TENSOR_MAP_SWIZZLE_128B); }
static void map_c(CUtensorMap* m, const void* p, int N) { map2d(m, p, N, S_, 64, 16, CU_TENSOR_MAP_SWIZZLE_128B); }

extern "C" void kernel_launch(void* const* d_in, const int* in_sizes, int n_in, void* d_out, int out_size) {
  const bf16* x = (const bf16*)d_in[0];
  const bf16* mem0 = (const bf16*)d_in[1];
  const bf16* Wo = (const bf16*)d_in[5];
  const bf16* w1 = (const bf16*)d_in[8];
  const bf16* w2 = (const bf16*)d_in[9];
  const bf16* w3 = (const bf16*)d_in[10];
  const bf16* w4 = (const bf16*)d_in[11];
  if (!g_encode) {
    void* fn = nullptr;
    cudaDriverEntryPointQueryResult qr;
    cudaGetDriverEntryPoint("cuTensorMapEncodeTiled", &fn, cudaEnableDefault, &qr);
    g_encode = (EncodeFn)fn;
    cudaFuncSetAttribute(k_gemm, cudaFuncAttributeMaxDynamicSharedMemorySize, G_SMEM);
    cudaFuncSetAttribute(k_rec, cudaFuncAttributeMaxDynamicSharedMemorySize, R_SMEM);
  }
  const bf16 *xn = (bf16*)sym(g_xn), *xn2 = (bf16*)sym(g_xn2), *gate = (bf16*)sym(g_gate), *ox = (bf16*)sym(g_ox),
             *h1 = (bf16*)sym(g_h1), *x1 = (bf16*)sym(g_x1), *ln1 = (bf16*)sym(g_ln1), *h3 = (bf16*)sym(g_h3);
  GemmMaps gm;
  map_a(&gm.a[0], xn2, D_); map_a(&gm.a[1], h1, D_); map_a(&gm.a[2], ln1, D_); map_a(&gm.a[3], h3, F_); map_a(&gm.a[4], ox, 4096);
  map_w(&gm.b[0], w1, D_, D_); map_w(&gm.b[1], w2, D_, D_); map_w(&gm.b[2], w3, F_, D_); map_w(&gm.b[3], w4, D_, F_);
  map_w(&gm.b[4], Wo, D_, 4096);
  map_c(&gm.c[0], h1, D_); map_c(&gm.c[1], x1, D_); map_c(&gm.c[2], h3, F_); map_c(&gm.c[3], gate, D_); map_c(&gm.c[4], d_out, D_);
  map_c(&gm.c[5], ln1, D_);
  map_a(&gm.e[0], xn, D_); map_a(&gm.e[1], x1, D_); map_a(&gm.e[2], gate, D_); map_a(&gm.e[3], x, D_);
  map2d(&gm.wd, Wo, D_, 4096, 64, 64, CU_TENSOR_MAP_SWIZZLE_128B);
  map_seg(&gm.od, ox, 4096, 4, 2, PROMO);
  RecMaps rm;
  for (int i = 0; i < 3; i++) {
    map2d(&rm.w[i], d_in[2 + i], 4096, D_, 64, 16, CU_TENSOR_MAP_SWIZZLE_128B);
    map2d(&rm.wb[i], d_in[2 + i], 4096, D_, 64, 256, CU_TENSOR_MAP_SWIZZLE_128B);
  }
  map2d(&rm.wo, Wo, D_, 4096, 64, 128, CU_TENSOR_MAP_SWIZZLE_128B);
  map2d(&rm.xn, xn, D_, S_, 64, 32, CU_TENSOR_MAP_SWIZZLE_128B);
  map_seg(&rm.xn1, xn, D_, 2, 1); map_seg(&rm.xn2, xn, D_, 2, 2);
  map2d(&rm.ox, ox, 4096, S_, 16, 32, CU_TENSOR_MAP_SWIZZLE_32B);
  unsigned char* xch = (unsigned char*)(((uintptr_t)sym(g_xch) + 2 * XPAGE - 1) & ~(uintptr_t)(2 * XPAGE - 1));
  cudaLaunchAttribute at[1];
  at[0].id = cudaLaunchAttributeClusterDimension;
  at[0].val.clusterDim.x = 6; at[0].val.clusterDim.y = 1; at[0].val.clusterDim.z = 1;
  cudaLaunchConfig_t cfg = {};
  cfg.attrs = at; cfg.numAttrs = 1; cfg.stream = cudaStreamPerThread;
  cfg.gridDim = dim3(96); cfg.blockDim = dim3(384); cfg.dynamicSmemBytes = R_SMEM;
  cudaLaunchKernelEx(&cfg, k_rec, rm, x, mem0, xch);
  at[0].id = cudaLaunchAttributeProgrammaticStreamSerialization;
  at[0].val.programmaticStreamSerializationAllowed = 1;
  cfg.gridDim = dim3(2 * NPAIR); cfg.dynamicSmemBytes = G_SMEM;
  cudaLaunchKernelEx(&cfg, k_gemm, gm, x, (bf16*)d_out);
}
```

```cpp
#include <cuda_runtime.h>
#include <cuda_bf16.h>
#include <cuda.h>
#include <stdint.h>

typedef __nv_bfloat16 bf16;

constexpr int S_ = 2048, D_ = 1024, H_ = 32, DH_ = 128, F_ = 3584, NSEG = 64;

__device__ __align__(1024) bf16 g_xn[S_ * D_];
__device__ __align__(1024) bf16 g_xn2[S_ * D_];
__device__ __align__(1024) bf16 g_ox[S_ * H_ * DH_];
__device__ __align__(1024) bf16 g_h1[S_ * D_];
__device__ __align__(1024) bf16 g_x1[S_ * D_];
__device__ __align__(1024) bf16 g_ln1[S_ * D_];
__device__ __align__(1024) bf16 g_h3[S_ * F_];
__device__ __align__(1024) bf16 g_gate[S_ * D_];
__device__ __align__(1024) uint4 g_dx[32 * 16 * 512];
__device__ __align__(1024) uint2 g_rstat[S_ * 4];

constexpr int XPAGE = 1 << 21;
__device__ __align__(4096) unsigned char g_xch[4 * XPAGE];
__device__ __forceinline__ uint32_t xchunk(int c, int p) { return (uint32_t)(c | ((__popc(c & 0xb3) & 1) ^ p)) << 12; }

#define TR(i)
#define TRB(i)
#define TRX(i, v)
#define TRV(i, v)
#define TG(r, i)
#define TRCAL(k)
#define ST(i)
__device__ __forceinline__ uint32_t smem_u32(const void* p) { return (uint32_t)__cvta_generic_to_shared(p); }
__device__ __forceinline__ void mbar_init(uint32_t bar, int cnt) {
  asm volatile("mbarrier.init.shared::cta.b64 [%0], %1;" ::"r"(bar), "r"(cnt) : "memory");
}
__device__ __forceinline__ void mbar_expect_tx(uint32_t bar, int bytes) {
  asm volatile("mbarrier.arrive.expect_tx.shared::cta.b64 _, [%0], %1;" ::"r"(bar), "r"(bytes) : "memory");
}
__device__ __forceinline__ void mbar_arrive(uint32_t bar) {
  asm volatile("mbarrier.arrive.shared::cta.b64 _, [%0];" ::"r"(bar) : "memory");
}
__device__ __forceinline__ void mbar_wait(uint32_t bar, uint32_t parity) {
  uint32_t ok;
  int n = 0;
  do {
    asm volatile(
        "{.reg .pred p; mbarrier.try_wait.parity.shared::cta.b64 p, [%1], %2; selp.u32 %0, 1, 0, p;}"
        : "=r"(ok) : "r"(bar), "r"(parity) : "memory");
  } while (!ok && ++n < (1 << 22));
}
__device__ __forceinline__ void mbar_wait_long(uint32_t bar, uint32_t parity) {
  uint32_t ok;
  int n = 0;
#pragma unroll 1
  do {
    asm volatile(
        "{.reg .pred p; mbarrier.try_wait.parity.shared::cta.b64 p, [%1], %2, 2000; selp.u32 %0, 1, 0, p;}"
        : "=r"(ok) : "r"(bar), "r"(parity) : "memory");
  } while (!ok && ++n < (1 << 22));
}
__device__ __forceinline__ void tma_load_2d(uint32_t dst, const CUtensorMap* m, int c0, int c1, uint32_t bar) {
  asm volatile(
      "cp.async.bulk.tensor.2d.shared::cluster.global.mbarrier::complete_tx::bytes [%0], [%1, {%3, %4}], [%2];"
      ::"r"(dst), "l"(m), "r"(bar), "r"(c0), "r"(c1) : "memory");
}
__device__ __forceinline__ void tma_load_2d_ef(uint32_t dst, const CUtensorMap* m, int c0, int c1, uint32_t bar) {
  asm volatile(
      "{.reg .b64 pol; createpolicy.fractional.L2::evict_first.b64 pol, 1.0;\n"
      "cp.async.bulk.tensor.2d.shared::cluster.global.mbarrier::complete_tx::bytes.L2::cache_hint [%0], [%1, {%3, %4}], [%2], pol;}"
      ::"r"(dst), "l"(m), "r"(bar), "r"(c0), "r"(c1) : "memory");
}
__device__ __forceinline__ void tma_load_3d(uint32_t dst, const CUtensorMap* m, int c0, int c1, int c2, uint32_t bar) {
  asm volatile(
      "cp.async.bulk.tensor.3d.shared::cluster.global.mbarrier::complete_tx::bytes [%0], [%1, {%3, %4, %5}], [%2];"
      ::"r"(dst), "l"(m), "r"(bar), "r"(c0), "r"(c1), "r"(c2) : "memory");
}
__device__ __forceinline__ void tma_store_2d(const CUtensorMap* m, uint32_t src, int c0, int c1) {
  asm volatile("cp.async.bulk.tensor.2d.global.shared::cta.bulk_group [%0, {%2, %3}], [%1];"
               ::"l"(m), "r"(src), "r"(c0), "r"(c1) : "memory");
}
__device__ __forceinline__ uint64_t policy(bool stream) {
  uint64_t a, b;
  asm("createpolicy.fractional.L2::evict_first.b64 %0, 1.0;" : "=l"(a));
  asm("createpolicy.fractional.L2::evict_normal.b64 %0, 1.0;" : "=l"(b));
  return stream ? a : b;
}
__device__ __forceinline__ void tma_store_2d_p(const CUtensorMap* m, uint32_t src, int c0, int c1, uint64_t pol) {
  asm volatile("cp.async.bulk.tensor.2d.global.shared::cta.bulk_group.L2::cache_hint [%0, {%2, %3}], [%1], %4;"
               ::"l"(m), "r"(src), "r"(c0), "r"(c1), "l"(pol) : "memory");
}
__device__ __forceinline__ void tma_prefetch_2d(const CUtensorMap* m, int c0, int c1) {
  asm volatile("cp.async.bulk.prefetch.tensor.2d.L2.global [%0, {%1, %2}];" ::"l"(m), "r"(c0), "r"(c1) : "memory");
}
__device__ __forceinline__ void tma_prefetch_3d(const CUtensorMap* m, int c0, int c1, int c2) {
  asm volatile("cp.async.bulk.prefetch.tensor.3d.L2.global [%0, {%1, %2, %3}];" ::"l"(m), "r"(c0), "r"(c1), "r"(c2) : "memory");
}
__device__ __forceinline__ uint32_t clk32() { uint32_t c; asm volatile("mov.u32 %0, %%clock;" : "=r"(c)::"memory"); return c; }
__device__ __forceinline__ uint32_t ld_rlx1(const void* p) { uint32_t v; asm volatile("ld.relaxed.gpu.global.u32 %0, [%1];" : "=r"(v) : "l"(p) : "memory"); return v; }
__device__ __forceinline__ uint32_t smid() { uint32_t c; asm volatile("mov.u32 %0, %%smid;" : "=r"(c)); return c; }
__device__ __forceinline__ void fence_async_smem() { asm volatile("fence.proxy.async.shared::cta;" ::: "memory"); }
__device__ __forceinline__ void bar_sync(int id, int n) { asm volatile("bar.sync %0, %1;" ::"r"(id), "r"(n) : "memory"); }
__device__ __forceinline__ void bar_arrive(int id, int n) { asm volatile("bar.arrive %0, %1;" ::"r"(id), "r"(n) : "memory"); }
__host__ __device__ constexpr uint64_t make_desc(uint32_t addr, uint32_t lbo, uint32_t sbo, uint32_t mode) {
  return (uint64_t)((addr & 0x3FFFF) >> 4) | ((uint64_t)(lbo >> 4) << 16) | ((uint64_t)(sbo >> 4) << 32) |
         ((uint64_t)mode << 62);
}
#define WG_FENCE() asm volatile("wgmma.fence.sync.aligned;" ::: "memory")
#define WG_COMMIT() asm volatile("wgmma.commit_group.sync.aligned;" ::: "memory")
#define WG_WAIT(n) asm volatile("wgmma.wait_group.sync.aligned " #n ";" ::: "memory")

__device__ __forceinline__ uint32_t pack_bf16(float lo, float hi) {
  uint32_t r;
  asm("cvt.rn.bf16x2.f32 %0, %1, %2;" : "=r"(r) : "f"(hi), "f"(lo));
  return r;
}
__device__ __forceinline__ float bf_lo(uint32_t v) { return __uint_as_float(v << 16); }
__device__ __forceinline__ float bf_hi(uint32_t v) { return __uint_as_float(v & 0xffff0000u); }
__device__ __forceinline__ float rbf(float x) { return __bfloat162float(__float2bfloat16_rn(x)); }

__device__ __forceinline__ void ldsm4(uint32_t* r, uint32_t a) {
  asm volatile("ldmatrix.sync.aligned.m8n8.x4.shared.b16 {%0,%1,%2,%3}, [%4];"
               : "=r"(r[0]), "=r"(r[1]), "=r"(r[2]), "=r"(r[3]) : "r"(a) : "memory");
}
__device__ __forceinline__ void ldsm4t(uint32_t* r, uint32_t a) {
  asm volatile("ldmatrix.sync.aligned.m8n8.x4.trans.shared.b16 {%0,%1,%2,%3}, [%4];"
               : "=r"(r[0]), "=r"(r[1]), "=r"(r[2]), "=r"(r[3]) : "r"(a) : "memory");
}
__device__ __forceinline__ void stsm4(uint32_t a, uint32_t r0, uint32_t r1, uint32_t r2, uint32_t r3) {
  asm volatile("stmatrix.sync.aligned.m8n8.x4.shared.b16 [%0], {%1,%2,%3,%4};"
               ::"r"(a), "r"(r0), "r"(r1), "r"(r2), "r"(r3) : "memory");
}
__device__ __forceinline__ void stsm4t(uint32_t a, uint32_t r0, uint32_t r1, uint32_t r2, uint32_t r3) {
  asm volatile("stmatrix.sync.aligned.m8n8.x4.trans.shared.b16 [%0], {%1,%2,%3,%4};"
               ::"r"(a), "r"(r0), "r"(r1), "r"(r2), "r"(r3) : "memory");
}
__device__ __forceinline__ void mma16816(float* d, uint32_t a0, uint32_t a1, uint32_t a2, uint32_t a3, uint32_t b0,
                                         uint32_t b1) {
  asm(
      "mma.sync.aligned.m16n8k16.row.col.f32.bf16.bf16.f32 {%0,%1,%2,%3}, {%4,%5,%6,%7}, {%8,%9}, {%0,%1,%2,%3};"
      : "+f"(d[0]), "+f"(d[1]), "+f"(d[2]), "+f"(d[3]) : "r"(a0), "r"(a1), "r"(a2), "r"(a3), "r"(b0), "r"(b1));
}
__device__ __forceinline__ void mma16816c(float* d, const float* c, uint32_t a0, uint32_t a1, uint32_t a2, uint32_t a3,
                                          uint32_t b0, uint32_t b1) {
  asm volatile(
      "mma.sync.aligned.m16n8k16.row.col.f32.bf16.bf16.f32 {%0,%1,%2,%3}, {%4,%5,%6,%7}, {%8,%9}, {%10,%11,%12,%13};"
      : "=f"(d[0]), "=f"(d[1]), "=f"(d[2]), "=f"(d[3])
      : "r"(a0), "r"(a1), "r"(a2), "r"(a3), "r"(b0), "r"(b1), "f"(c[0]), "f"(c[1]), "f"(c[2]), "f"(c[3]));
}
__device__ __forceinline__ void mma1688(float* d, uint32_t a0, uint32_t a1, uint32_t b0) {
  asm("mma.sync.aligned.m16n8k8.row.col.f32.bf16.bf16.f32 {%0,%1,%2,%3}, {%4,%5}, {%6}, {%0,%1,%2,%3};"
               : "+f"(d[0]), "+f"(d[1]), "+f"(d[2]), "+f"(d[3]) : "r"(a0), "r"(a1), "r"(b0));
}
__device__ __forceinline__ void wgmma_n8_tt(float* d, uint64_t a, uint64_t b, int scale_d) {
  asm volatile(
      "{.reg .pred p; setp.ne.b32 p, %6, 0;\n"
      "wgmma.mma_async.sync.aligned.m64n8k16.f32.bf16.bf16 {%0,%1,%2,%3}, %4, %5, p, 1, 1, 1, 1;}"
      : "+f"(d[0]), "+f"(d[1]), "+f"(d[2]), "+f"(d[3]) : "l"(a), "l"(b), "r"(scale_d));
}
__device__ __forceinline__ void wgmma_n256(float* d, uint64_t a, uint64_t b, int scale_d) {
  asm volatile(
      "{.reg .pred p; setp.ne.b32 p, %130, 0;\n"
      "wgmma.mma_async.sync.aligned.m64n256k16.f32.bf16.bf16 "
      "{%0,%1,%2,%3,%4,%5,%6,%7,%8,%9,%10,%11,%12,%13,%14,%15,%16,%17,%18,%19,%20,%21,%22,%23,%24,%25,%26,%27,%28,%29,%30,%31,"
      "%32,%33,%34,%35,%36,%37,%38,%39,%40,%41,%42,%43,%44,%45,%46,%47,%48,%49,%50,%51,%52,%53,%54,%55,%56,%57,%58,%59,%60,%61,%62,%63,"
      "%64,%65,%66,%67,%68,%69,%70,%71,%72,%73,%74,%75,%76,%77,%78,%79,%80,%81,%82,%83,%84,%85,%86,%87,%88,%89,%90,%91,%92,%93,%94,%95,"
      "%96,%97,%98,%99,%100,%101,%102,%103,%104,%105,%106,%107,%108,%109,%110,%111,%112,%113,%114,%115,%116,%117,%118,%119,%120,%121,%122,%123,%124,%125,%126,%127},"
      " %128, %129, p, 1, 1, 0, 1;}"
      : "+f"(d[0]), "+f"(d[1]), "+f"(d[2]), "+f"(d[3]), "+f"(d[4]), "+f"(d[5]), "+f"(d[6]), "+f"(d[7]),
        "+f"(d[8]), "+f"(d[9]), "+f"(d[10]), "+f"(d[11]), "+f"(d[12]), "+f"(d[13]), "+f"(d[14]), "+f"(d[15]),
        "+f"(d[16]), "+f"(d[17]), "+f"(d[18]), "+f"(d[19]), "+f"(d[20]), "+f"(d[21]), "+f"(d[22]), "+f"(d[23]),
        "+f"(d[24]), "+f"(d[25]), "+f"(d[26]), "+f"(d[27]), "+f"(d[28]), "+f"(d[29]), "+f"(d[30]), "+f"(d[31]),
        "+f"(d[32]), "+f"(d[33]), "+f"(d[34]), "+f"(d[35]), "+f"(d[36]), "+f"(d[37]), "+f"(d[38]), "+f"(d[39]),
        "+f"(d[40]), "+f"(d[41]), "+f"(d[42]), "+f"(d[43]), "+f"(d[44]), "+f"(d[45]), "+f"(d[46]), "+f"(d[47]),
        "+f"(d[48]), "+f"(d[49]), "+f"(d[50]), "+f"(d[51]), "+f"(d[52]), "+f"(d[53]), "+f"(d[54]), "+f"(d[55]),
        "+f"(d[56]), "+f"(d[57]), "+f"(d[58]), "+f"(d[59]), "+f"(d[60]), "+f"(d[61]), "+f"(d[62]), "+f"(d[63]),
        "+f"(d[64]), "+f"(d[65]), "+f"(d[66]), "+f"(d[67]), "+f"(d[68]), "+f"(d[69]), "+f"(d[70]), "+f"(d[71]),
        "+f"(d[72]), "+f"(d[73]), "+f"(d[74]), "+f"(d[75]), "+f"(d[76]), "+f"(d[77]), "+f"(d[78]), "+f"(d[79]),
        "+f"(d[80]), "+f"(d[81]), "+f"(d[82]), "+f"(d[83]), "+f"(d[84]), "+f"(d[85]), "+f"(d[86]), "+f"(d[87]),
        "+f"(d[88]), "+f"(d[89]), "+f"(d[90]), "+f"(d[91]), "+f"(d[92]), "+f"(d[93]), "+f"(d[94]), "+f"(d[95]),
        "+f"(d[96]), "+f"(d[97]), "+f"(d[98]), "+f"(d[99]), "+f"(d[100]), "+f"(d[101]), "+f"(d[102]), "+f"(d[103]),
        "+f"(d[104]), "+f"(d[105]), "+f"(d[106]), "+f"(d[107]), "+f"(d[108]), "+f"(d[109]), "+f"(d[110]), "+f"(d[111]),
        "+f"(d[112]), "+f"(d[113]), "+f"(d[114]), "+f"(d[115]), "+f"(d[116]), "+f"(d[117]), "+f"(d[118]), "+f"(d[119]),
        "+f"(d[120]), "+f"(d[121]), "+f"(d[122]), "+f"(d[123]), "+f"(d[124]), "+f"(d[125]), "+f"(d[126]), "+f"(d[127])
      : "l"(a), "l"(b), "r"(scale_d));
}

__device__ __forceinline__ uint4 ld_rlx4(const void* p) {
  uint4 v;
  asm volatile("{.reg .b128 r; ld.relaxed.gpu.global.b128 r, [%4]; mov.b128 {%0,%1,%2,%3}, r;}"
               : "=r"(v.x), "=r"(v.y), "=r"(v.z), "=r"(v.w) : "l"(p) : "memory");
  return v;
}
__device__ __forceinline__ uint2 ld_rlx2(const void* p) {
  uint2 v;
  asm volatile("{.reg .b64 r; ld.relaxed.gpu.global.b64 r, [%2]; mov.b64 {%0,%1}, r;}" : "=r"(v.x), "=r"(v.y) : "l"(p) : "memory");
  return v;
}
__device__ __forceinline__ void st_rlx4(void* p, uint32_t a, uint32_t b, uint32_t c, uint32_t d) {
  asm volatile("{.reg .b128 r; mov.b128 r, {%1,%2,%3,%4}; st.relaxed.gpu.global.b128 [%0], r;}"
               ::"l"(p), "r"(a), "r"(b), "r"(c), "r"(d) : "memory");
}
__device__ __forceinline__ void st_rlx2(void* p, uint32_t a, uint32_t b) {
  asm volatile("{.reg .b64 r; mov.b64 r, {%1,%2}; st.relaxed.gpu.global.b64 [%0], r;}" ::"l"(p), "r"(a), "r"(b) : "memory");
}
__device__ __forceinline__ void st_rlx1(void* p, uint32_t a) {
  asm volatile("st.relaxed.gpu.global.u32 [%0], %1;" ::"l"(p), "r"(a) : "memory");
}

__device__ __forceinline__ uint32_t nz(uint32_t v) { return v == 0u ? 0x80000000u : v; }
__device__ __forceinline__ uint32_t tagu(uint32_t v, uint32_t tag) { return (v & ~1u) | tag; }
__device__ __forceinline__ float asf(uint32_t v) { return __uint_as_float(v); }
__device__ __forceinline__ uint32_t asu(float v) { return __float_as_uint(v); }
__device__ __forceinline__ uint32_t opaque(uint32_t x) { return __shfl_sync(~0u, x, threadIdx.x & 31); }
__device__ __forceinline__ unsigned char* xptr(uint32_t lo, uint32_t hi) {
  uint64_t a;
  asm("mov.b64 %0, {%1, %2};" : "=l"(a) : "r"(lo), "r"(hi));
  return (unsigned char*)a;
}
#define DSC(lo) (uint64_t)xptr(lo, (uint32_t)(make_desc(0, 0, 1024, 1) >> 32))
__device__ __forceinline__ void reld4(uint4& v, const void* p, uint32_t m) {
  asm volatile("{.reg .pred q; setp.eq.b32 q, %5, 0; @q ld.relaxed.gpu.global.v4.b32 {%0,%1,%2,%3}, [%4];}"
               : "+r"(v.x), "+r"(v.y), "+r"(v.z), "+r"(v.w) : "l"(p), "r"(m) : "memory");
}
__device__ __forceinline__ uint32_t ne2(uint32_t a, uint32_t b, uint32_t t) {
  uint32_t r;
  asm("lop3.b32 %0, %1, %2, %3, 0x7E;" : "=r"(r) : "r"(a), "r"(b), "r"(t));
  return r;
}
__device__ __forceinline__ uint32_t or3(uint32_t a, uint32_t b, uint32_t c) {
  uint32_t r;
  asm("lop3.b32 %0, %1, %2, %3, 0xFE;" : "=r"(r) : "r"(a), "r"(b), "r"(c));
  return r;
}
__device__ __forceinline__ uint32_t after(uint32_t a, uint32_t dep, uint32_t zero) {
  uint32_t r;
  asm("lop3.b32 %0, %1, %2, %3, 0xF8;" : "=r"(r) : "r"(a), "r"(dep), "r"(zero));
  return r;
}
__device__ __forceinline__ uint32_t wait_clk(uint32_t t, int D) {
  uint32_t c = clk32();
  if ((int)(t - c) < D) t = c + D;
  while ((int)(c - t) < 0) c = clk32();
  return c;
}
__device__ __forceinline__ uint2 timer_edge() {
  uint32_t g0, g;
  int n = 0;
  asm volatile("mov.u32 %0, %%globaltimer_lo;" : "=r"(g0)::"memory");
#pragma unroll 1
  do { asm volatile("mov.u32 %0, %%globaltimer_lo;" : "=r"(g)::"memory"); } while (g == g0 && ++n < 8);
  return make_uint2(g, clk32());
}
__device__ __forceinline__ float4 lds_f4(uint32_t a) {
  float4 v;
  asm volatile("ld.shared.v4.f32 {%0,%1,%2,%3}, [%4];" : "=f"(v.x), "=f"(v.y), "=f"(v.z), "=f"(v.w) : "r"(a) : "memory");
  return v;
}
__device__ __forceinline__ uint4 lds_u4(uint32_t a) {
  uint4 v;
  asm volatile("ld.shared.v4.u32 {%0,%1,%2,%3}, [%4];" : "=r"(v.x), "=r"(v.y), "=r"(v.z), "=r"(v.w) : "r"(a) : "memory");
  return v;
}
__device__ __forceinline__ uint2 lds_u2(uint32_t a) {
  uint2 v;
  asm volatile("ld.shared.v2.u32 {%0,%1}, [%2];" : "=r"(v.x), "=r"(v.y) : "r"(a) : "memory");
  return v;
}
__device__ __forceinline__ uint32_t lds_u1(uint32_t a) {
  uint32_t v;
  asm volatile("ld.shared.u32 %0, [%1];" : "=r"(v) : "r"(a) : "memory");
  return v;
}
__device__ __forceinline__ void sts_u4(uint32_t a, uint4 v) {
  asm volatile("st.shared.v4.u32 [%0], {%1,%2,%3,%4};" ::"r"(a), "r"(v.x), "r"(v.y), "r"(v.z), "r"(v.w) : "memory");
}
__device__ __forceinline__ void sts_f4(uint32_t a, const float* d) {
  asm volatile("st.shared.v4.f32 [%0], {%1,%2,%3,%4};" ::"r"(a), "f"(d[0]), "f"(d[1]), "f"(d[2]), "f"(d[3]) : "memory");
}
__device__ __forceinline__ void sts_u2(uint32_t a, uint32_t x, uint32_t y) {
  asm volatile("st.shared.v2.u32 [%0], {%1,%2};" ::"r"(a), "r"(x), "r"(y) : "memory");
}
__device__ __forceinline__ void sts_u1(uint32_t a, uint32_t v) {
  asm volatile("st.shared.u32 [%0], %1;" ::"r"(a), "r"(v) : "memory");
}
__device__ __forceinline__ void sta4(uint32_t a, uint4 v, uint32_t bar) {
  asm volatile("st.async.shared::cluster.mbarrier::complete_tx::bytes.v4.b32 [%0], {%1,%2,%3,%4}, [%5];"
               ::"r"(a), "r"(v.x), "r"(v.y), "r"(v.z), "r"(v.w), "r"(bar) : "memory");
}
__device__ __forceinline__ void sta2(uint32_t a, uint32_t x, uint32_t y, uint32_t bar) {
  asm volatile("st.async.shared::cluster.mbarrier::complete_tx::bytes.v2.b32 [%0], {%1,%2}, [%3];" ::"r"(a), "r"(x), "r"(y), "r"(bar) : "memory");
}
__device__ __forceinline__ void sta1(uint32_t a, uint32_t x, uint32_t bar) {
  asm volatile("st.async.shared::cluster.mbarrier::complete_tx::bytes.b32 [%0], %1, [%2];" ::"r"(a), "r"(x), "r"(bar) : "memory");
}
__device__ __forceinline__ void arrive_remote(uint32_t bar) {
  asm volatile("mbarrier.arrive.shared::cluster.b64 _, [%0];" ::"r"(bar) : "memory");
}
__device__ __forceinline__ uint32_t peer_base(uint32_t sb, int rank) {
  uint32_t r;
  asm("mapa.shared::cluster.u32 %0, %1, %2;" : "=r"(r) : "r"(sb), "r"(rank));
  return r - sb;
}
__device__ __forceinline__ float ex2(float x) { float r; asm("ex2.approx.ftz.f32 %0, %1;" : "=f"(r) : "f"(x)); return r; }
__device__ __forceinline__ float rcp(float x) { float r; asm("rcp.approx.ftz.f32 %0, %1;" : "=f"(r) : "f"(x)); return r; }
__device__ __forceinline__ uint32_t min4(uint4 v) { return min(__vimin3_u32(v.x, v.y, v.z), v.w); }

__device__ __forceinline__ void softmax_e(float* sc) {
  float mx = fmaxf(fmaxf(fmaxf(sc[0], sc[1]), fmaxf(sc[2], sc[3])), fmaxf(fmaxf(sc[4], sc[5]), fmaxf(sc[6], sc[7])));
  mx = fmaxf(mx, fmaxf(sc[8], sc[9]));
  const float m1 = __shfl_xor_sync(~0u, mx, 1), m2 = __shfl_xor_sync(~0u, mx, 2), m3 = __shfl_xor_sync(~0u, mx, 3);
  mx = fmaxf(fmaxf(mx, m1), fmaxf(m2, m3));
  const float c = 0.08838834764831845f * 1.4426950408889634f, mc = -mx * c;
#pragma unroll
  for (int i = 0; i < 10; i++) sc[i] = ex2(fmaf(sc[i], c, mc));
}
__device__ __forceinline__ void sum_scores(float* sc, uint2 u0, uint2 u1, uint32_t u2, uint2 v0, uint2 v1, uint32_t v2) {
  sc[0] = bf_lo(u0.x) + bf_lo(v0.x); sc[1] = bf_hi(u0.x) + bf_hi(v0.x);
  sc[2] = bf_lo(u0.y) + bf_lo(v0.y); sc[3] = bf_hi(u0.y) + bf_hi(v0.y);
  sc[4] = bf_lo(u1.x) + bf_lo(v1.x); sc[5] = bf_hi(u1.x) + bf_hi(v1.x);
  sc[6] = bf_lo(u1.y) + bf_lo(v1.y); sc[7] = bf_hi(u1.y) + bf_hi(v1.y);
  sc[8] = bf_lo(u2) + bf_lo(v2); sc[9] = bf_hi(u2) + bf_hi(v2);
}
__device__ __forceinline__ void pv_mma(float* o0, float* o1, float* sm, const uint4* vx, const uint2* m, const uint32_t* p) {
  const uint32_t one = 0x3F803F80u;
#pragma unroll
  for (int i = 0; i < 4; i++) o0[i] = o1[i] = sm[i] = 0.f;
  mma16816(sm, one, one, one, one, p[0], p[1]);
  mma16816(o0, vx[0].x, vx[0].y, vx[0].z, vx[0].w, p[0], p[1]);
  mma16816(o1, vx[1].x, vx[1].y, vx[1].z, vx[1].w, p[0], p[1]);
  mma16816(sm, one, one, one, one, p[2], p[3]);
  mma16816(o0, vx[2].x, vx[2].y, vx[2].z, vx[2].w, p[2], p[3]);
  mma16816(o1, vx[3].x, vx[3].y, vx[3].z, vx[3].w, p[2], p[3]);
  mma1688(sm, one, one, p[4]);
  mma16816(o0, m[0].x, m[0].y, m[1].x, m[1].y, p[4], p[4]);
  mma16816(o1, m[2].x, m[2].y, m[3].x, m[3].y, p[4], p[4]);
}
#define D16(d) "+f"(d[0]), "+f"(d[1]), "+f"(d[2]), "+f"(d[3]), "+f"(d[4]), "+f"(d[5]), "+f"(d[6]), "+f"(d[7]), "+f"(d[8]), \
               "+f"(d[9]), "+f"(d[10]), "+f"(d[11]), "+f"(d[12]), "+f"(d[13]), "+f"(d[14]), "+f"(d[15])
__device__ __forceinline__ void wgmma_rs32(float* d, const uint32_t* a, uint64_t b, int scale_d) {
  asm volatile(
      "{.reg .pred p; setp.ne.b32 p, %21, 0;\n"
      "wgmma.mma_async.sync.aligned.m64n32k16.f32.bf16.bf16 {%0,%1,%2,%3,%4,%5,%6,%7,%8,%9,%10,%11,%12,%13,%14,%15}, "
      "{%16,%17,%18,%19}, %20, p, 1, 1, 0;}"
      : D16(d) : "r"(a[0]), "r"(a[1]), "r"(a[2]), "r"(a[3]), "l"(b), "r"(scale_d));
}
__device__ __forceinline__ void wgmma_ss32(float* d, uint64_t a, uint64_t b, int scale_d) {
  asm volatile(
      "{.reg .pred p; setp.ne.b32 p, %18, 0;\n"
      "wgmma.mma_async.sync.aligned.m64n32k16.f32.bf16.bf16 {%0,%1,%2,%3,%4,%5,%6,%7,%8,%9,%10,%11,%12,%13,%14,%15}, "
      "%16, %17, p, 1, 1, 1, 0;}"
      : D16(d) : "l"(a), "l"(b), "r"(scale_d));
}
#define R32 "{%0,%1,%2,%3,%4,%5,%6,%7,%8,%9,%10,%11,%12,%13,%14,%15,%16,%17,%18,%19,%20,%21,%22,%23,%24,%25,%26,%27,%28,%29,%30,%31}, "
__device__ __forceinline__ void wgmma_rs64(float* d, const uint32_t* a, uint64_t b, int scale_d) {
  asm volatile("{.reg .pred p; setp.ne.b32 p, %37, 0;\nwgmma.mma_async.sync.aligned.m64n64k16.f32.bf16.bf16 " R32 "{%32,%33,%34,%35}, %36, p, 1, 1, 0;}"
               : D16(d), D16((d + 16)) : "r"(a[0]), "r"(a[1]), "r"(a[2]), "r"(a[3]), "l"(b), "r"(scale_d));
}
__device__ __forceinline__ void wgmma_ss64(float* d, uint64_t a, uint64_t b) {
  asm volatile("wgmma.mma_async.sync.aligned.m64n64k16.f32.bf16.bf16 " R32 "%32, %33, 1, 1, 1, 1, 0;" : D16(d), D16((d + 16)) : "l"(a), "l"(b));
}
__device__ __forceinline__ void wgmma_ss48(float* d, uint64_t a, uint64_t b, int scale_d) {
  asm volatile(
      "{.reg .pred p; setp.ne.b32 p, %26, 0;\n"
      "wgmma.mma_async.sync.aligned.m64n48k16.f32.bf16.bf16 {%0,%1,%2,%3,%4,%5,%6,%7,%8,%9,%10,%11,%12,%13,%14,%15,"
      "%16,%17,%18,%19,%20,%21,%22,%23}, %24, %25, p, 1, 1, 0, 0;}"
      : D16(d), "+f"(d[16]), "+f"(d[17]), "+f"(d[18]), "+f"(d[19]), "+f"(d[20]), "+f"(d[21]), "+f"(d[22]), "+f"(d[23])
      : "l"(a), "l"(b), "r"(scale_d));
}
enum { T_W1, T_W2, T_W3, T_W4, T_WO, T_LN };
constexpr int NPAIR = 18, G_STAGES = 4, G_STAGE_BYTES = 49152, G_STG = G_STAGES * G_STAGE_BYTES, G_BAR = G_STG + 32768,
              G_SMEM = G_BAR + 512;
constexpr int WAIT_LIM = 1 << 22;
#define NSLP 40
enum { C_H1 = 0, C_LN1 = 16, C_H3 = 32, C_G = 48, C_OX = 64, C_LN = 128, C_CHK, C_DONE, C_END };
__device__ __align__(128) unsigned g_cnt[C_END * 8];

struct GemmMaps { CUtensorMap a[5], b[5], c[6], e[4], od; };
__constant__ unsigned short c_list[NPAIR][24] = {
    {0x8d0, 0x4e8, 0x11, 0x39, 0x20a, 0x2da, 0x7a, 0x17a, 0x1aa, 0x2aa, 0x3, 0xb3, 0x414, 0x8000, 0x8000, 0x8000, 0x8000, 0x8000, 0x8000, 0x8000, 0x8000, 0x8000, 0x8000, 0x30},
    {0x448, 0x430, 0x99, 0x342, 0x202, 0x282, 0x31a, 0x26a, 0x72, 0x1ba, 0xb, 0xf3, 0x494, 0x8000, 0x8000, 0x8000, 0x8000, 0x8000, 0x8000, 0x8000, 0x8000, 0x8000, 0x8000, 0x30},
    {0x408, 0x801, 0xe1, 0x1c2, 0x112, 0x312, 0x36a, 0x1a, 0x2b2, 0x16a, 0x5b, 0x33, 0x424, 0x8000, 0x8000, 0x8000, 0x8000, 0x8000, 0x8000, 0x8000, 0x8000, 0x8000, 0x8000, 0x30},
    {0x4c8, 0x841, 0xa9, 0x182, 0x4a, 0xaa, 0xb2, 0x29a, 0x362, 0x2ba, 0x93, 0xe3, 0x49c, 0x8000, 0x8000, 0x8000, 0x8000, 0x8000, 0x8000, 0x8000, 0x8000, 0x8000, 0x8000, 0x30},
    {0x488, 0x4f0, 0x19, 0x31, 0x28a, 0x262, 0x212, 0x122, 0x372, 0x272, 0x83, 0x73, 0x444, 0x8000, 0x8000, 0x8000, 0x8000, 0x8000, 0x8000, 0x8000, 0x8000, 0x8000, 0x8000, 0x30},
    {0x890, 0x468, 0x59, 0xb1, 0x34a, 0x12, 0xd2, 0x13a, 0xf2, 0x1f2, 0x9b, 0x2b, 0x44c, 0x8000, 0x8000, 0x8000, 0x8000, 0x8000, 0x8000, 0x8000, 0x8000, 0x8000, 0x8000, 0x30},
    {0x440, 0x8c1, 0x61, 0x2, 0x352, 0x52, 0x2d2, 0x23a, 0x62, 0xea, 0x1b, 0x23, 0x4d4, 0x8000, 0x8000, 0x8000, 0x8000, 0x8000, 0x8000, 0x8000, 0x8000, 0x8000, 0x8000, 0x30},
    {0x4c0, 0x881, 0x29, 0x102, 0x18a, 0x192, 0x252, 0x1ea, 0x22a, 0x222, 0xdb, 0x7b, 0x40c, 0x8000, 0x8000, 0x8000, 0x8000, 0x8000, 0x8000, 0x8000, 0x8000, 0x8000, 0x8000, 0x30},
    {0x18, 0x8b8, 0x889, 0xb9, 0x2ca, 0x2e2, 0x10a, 0x1e2, 0xa2, 0xd3, 0x6b, 0x41c, 0x8000, 0x8000, 0x8000, 0x8000, 0x8000, 0x8000, 0x8000, 0x8000, 0x8000, 0x8000, 0x8000, 0x28},
    {0x98, 0x460, 0x91, 0xf9, 0xca, 0x1d2, 0x37a, 0x35a, 0x32a, 0x1b2, 0x2f2, 0x332, 0xc4, 0x4e4, 0x8000, 0x8000, 0x8000, 0x8000, 0x8000, 0x8000, 0x8000, 0x8000, 0x8000, 0x28},
    {0x400, 0x4b0, 0xa1, 0xc2, 0x24a, 0x25a, 0x292, 0x162, 0x2ea, 0x53, 0xa3, 0x4a4, 0x8000, 0x8000, 0x8000, 0x8000, 0x8000, 0x8000, 0x8000, 0x8000, 0x8000, 0x8000, 0x8000, 0x28},
    {0x850, 0x428, 0x21, 0x42, 0x242, 0x2a2, 0x1fa, 0xfa, 0x32, 0x43, 0x63, 0x4dc, 0x8000, 0x8000, 0x8000, 0x8000, 0x8000, 0x8000, 0x8000, 0x8000, 0x8000, 0x8000, 0x8000, 0x28},
    {0xe0, 0xf8, 0xc9, 0x69, 0x142, 0x9a, 0x82, 0x27a, 0xda, 0x4b, 0xeb, 0x4cc, 0x8000, 0x8000, 0x8000, 0x8000, 0x8000, 0x8000, 0x8000, 0x8000, 0x8000, 0x8000, 0x8000, 0x28},
    {0x20, 0x78, 0x9, 0xe9, 0x302, 0x21a, 0x2a, 0xba, 0x15a, 0xcb, 0xfb, 0x404, 0x8000, 0x8000, 0x8000, 0x8000, 0x8000, 0x8000, 0x8000, 0x8000, 0x8000, 0x8000, 0x8000, 0x28},
    {0x810, 0x4a8, 0x51, 0x79, 0x14a, 0x92, 0x19a, 0x3a, 0x322, 0x33a, 0x232, 0x132, 0x54, 0x45c, 0x8000, 0x8000, 0x8000, 0x8000, 0x8000, 0x8000, 0x8000, 0x8000, 0x8000, 0x28},
    {0x480, 0x470, 0xd9, 0x2c2, 0x1ca, 0x1da, 0x5a, 0x1a2, 0x6a, 0x8b, 0xab, 0x484, 0x8000, 0x8000, 0x8000, 0x8000, 0x8000, 0x8000, 0x8000, 0x8000, 0x8000, 0x8000, 0x8000, 0x28},
    {0x58, 0x838, 0x849, 0xf1, 0x8a, 0x30a, 0x12a, 0x2fa, 0x22, 0x13, 0xbb, 0x64, 0x42c, 0x8000, 0x8000, 0x8000, 0x8000, 0x8000, 0x8000, 0x8000, 0x8000, 0x8000, 0x8000, 0x40},
    {0xd8, 0x4a0, 0xd1, 0x71, 0xa, 0x152, 0x11a, 0xe2, 0x172, 0xc3, 0x3b, 0x8c, 0x46c, 0x8000, 0x8000, 0x8000, 0x8000, 0x8000, 0x8000, 0x8000, 0x8000, 0x8000, 0x8000, 0x40},
};
struct Tile { int valid, ty, mp, nt, flush, nkb; };
__device__ __forceinline__ Tile decode(int v) {
  Tile t;
  t.valid = v < 0x8000; t.ty = v & 7; t.mp = (v >> 3) & 7; t.nt = (v >> 6) & 15; t.flush = (v >> 10) & 3;
  t.nkb = t.ty == T_W4 ? 56 : (t.ty == T_WO ? 64 : 16);
  return t;
}
__device__ __forceinline__ unsigned ld_acq(int c) {
  unsigned v;
  asm volatile("ld.acquire.gpu.global.u32 %0, [%1];" : "=r"(v) : "l"(g_cnt + c * 8) : "memory");
  return v;
}
__device__ __forceinline__ void wait_cnt(int c, unsigned target) {
  unsigned v;
  int n = 0;
#pragma unroll 1
  do {
    v = ld_acq(c);
    if (v >= target) break;
    __nanosleep(NSLP);
  } while (++n < WAIT_LIM);
}
__device__ __forceinline__ void sig_cnt(int c, int v = 1) {
  asm volatile("red.release.gpu.global.add.u32 [%0], %1;" ::"l"(g_cnt + c * 8), "r"(v) : "memory");
}
__device__ __forceinline__ void fence_async_all() { asm volatile("fence.proxy.async.global;" ::: "memory"); }
__device__ __forceinline__ void arrive_both(uint32_t bar) {
  asm volatile(
      "{.reg .b32 r0, r1; mapa.shared::cluster.u32 r0, %0, 0; mapa.shared::cluster.u32 r1, %0, 1;\n"
      "mbarrier.arrive.shared::cluster.b64 _, [r0];\n"
      "mbarrier.arrive.shared::cluster.b64 _, [r1];}" ::"r"(bar) : "memory");
}
__device__ __forceinline__ void load_b(uint32_t dst, const CUtensorMap* m, int k, int ng, uint32_t bar) {
  asm volatile(
      "cp.async.bulk.tensor.3d.shared::cluster.global.mbarrier::complete_tx::bytes.multicast::cluster [%0], [%1, {%3, %4, %5}], [%2], %6;"
      ::"r"(dst), "l"(m), "r"(bar), "r"(0), "r"(k), "r"(ng), "h"((uint16_t)3) : "memory");
}
__device__ __forceinline__ float gelu_f(float x) {
  float u = x * (0.7978845608f + 0.0356774081f * x * x), t;
  asm("tanh.approx.f32 %0, %1;" : "=f"(t) : "f"(u));
  return fmaf(x, t, x);
}
__device__ __forceinline__ float silu_f(float x) {
  float hx = 0.5f * x, t;
  asm("tanh.approx.f32 %0, %1;" : "=f"(t) : "f"(hx));
  return fmaf(hx, t, hx);
}

__device__ __forceinline__ uint32_t add2(uint32_t a, uint32_t b) { uint32_t r; asm("add.rn.bf16x2 %0, %1, %2;" : "=r"(r) : "r"(a), "r"(b)); return r; }
__device__ __forceinline__ uint32_t mul2(uint32_t a, uint32_t b) { uint32_t r; asm("mul.rn.bf16x2 %0, %1, %2;" : "=r"(r) : "r"(a), "r"(b)); return r; }
__device__ __forceinline__ uint32_t fma2(uint32_t a, uint32_t b, uint32_t c) { uint32_t r; asm("fma.rn.bf16x2 %0, %1, %2, %3;" : "=r"(r) : "r"(a), "r"(b), "r"(c)); return r; }

__device__ __forceinline__ uint32_t scale2(uint32_t d, uint32_t hi, uint32_t lo) {
  uint32_t r;
  asm("fma.rn.bf16x2 %0, %1, %2, %3;" : "=r"(r) : "r"(d), "r"(hi), "r"(mul2(d, lo)));
  return r;
}
__device__ __forceinline__ void split2(float s, uint32_t& hi, uint32_t& lo) {
  hi = pack_bf16(s, s);
  const float r = s - bf_lo(hi);
  lo = pack_bf16(r, r);
}
__device__ __forceinline__ float ln_inv(float m2) {
  float sd, inv;
  asm("sqrt.approx.f32 %0, %1;" : "=f"(sd) : "f"(rbf(rbf(m2 * (1.f / 1024.f)) + 1e-5f)));
  asm("rcp.approx.f32 %0, %1;" : "=f"(inv) : "f"(rbf(sd)));
  return inv;
}
__device__ __forceinline__ void ln_packed(uint32_t* u) {
  float s = 0.f, s2 = 0.f;
#pragma unroll
  for (int i = 0; i < 16; i++) { s += bf_lo(u[i]); s2 += bf_hi(u[i]); }
  s += s2;
#pragma unroll
  for (int o = 16; o > 0; o >>= 1) s += __shfl_xor_sync(~0u, s, o);
  float mean = s * (1.f / 1024.f), q = 0.f, q2 = 0.f;
#pragma unroll
  for (int i = 0; i < 16; i++) { float a = bf_lo(u[i]) - mean, b = bf_hi(u[i]) - mean; q = fmaf(a, a, q); q2 = fmaf(b, b, q2); }
  q += q2;
#pragma unroll
  for (int o = 16; o > 0; o >>= 1) q += __shfl_xor_sync(~0u, q, o);
  const uint32_t nmb = pack_bf16(-mean, -mean);
  uint32_t hi, lo;
  split2(ln_inv(q), hi, lo);
#pragma unroll
  for (int i = 0; i < 16; i++) u[i] = scale2(add2(u[i], nmb), hi, lo);
}
__device__ __forceinline__ void row_ld(uint32_t* u, const bf16* p, int lane) {
#pragma unroll
  for (int i = 0; i < 4; i++) {
    uint4 v = __ldcg((const uint4*)(p + i * 256 + lane * 8));
    u[i * 4] = v.x; u[i * 4 + 1] = v.y; u[i * 4 + 2] = v.z; u[i * 4 + 3] = v.w;
  }
}
__device__ __forceinline__ void row_st(const uint32_t* u, bf16* p, int lane) {
#pragma unroll
  for (int i = 0; i < 4; i++) *(uint4*)(p + i * 256 + lane * 8) = make_uint4(u[i * 4], u[i * 4 + 1], u[i * 4 + 2], u[i * 4 + 3]);
}

template <int N>
__device__ __forceinline__ void activate(uint32_t* pk, int act) {
  if (act == T_W1 || act == T_W3) {
#pragma unroll
    for (int i = 0; i < N; i++) pk[i] = pack_bf16(gelu_f(bf_lo(pk[i])), gelu_f(bf_hi(pk[i])));
  } else if (act == T_W4) {
#pragma unroll
    for (int i = 0; i < N; i++) pk[i] = pack_bf16(silu_f(bf_lo(pk[i])), silu_f(bf_hi(pk[i])));
  }
}
__device__ __forceinline__ void epi_store(const uint32_t* pk, uint32_t bf, uint32_t xo, const CUtensorMap* cm, int col, int row, int lane) {
  if (lane == 0) asm volatile("cp.async.bulk.wait_group.read 1;" ::: "memory");
  __syncwarp();
#pragma unroll
  for (int q = 0; q < 4; q++) stsm4(bf + (xo ^ (q << 5)), pk[q * 4], pk[q * 4 + 1], pk[q * 4 + 2], pk[q * 4 + 3]);
  fence_async_smem();
  __syncwarp();
  if (lane == 0) {
    tma_store_2d(cm, bf, col, row);
    asm volatile("cp.async.bulk.commit_group;" ::: "memory");
  }
}

#define DP0 3
#define DPK 4
#define DPS 1
#define DST 5
#define NA0 5
#define NA1 11
#define PP 3
#define DQ 2
constexpr int NRD = 5, D_STAGES = DST, D_W = 0, D_RING = 2 * (8 - NRD) * 16384, D_SUM = D_RING + 5 * 16384;
static_assert(D_SUM + 16384 <= G_STG, "smem");
__device__ constexpr int d_head(int i) { return i < DQ ? i : (i < DQ + 8 - NRD ? i + NRD - DQ : i - 8 + NRD); }

__global__ void __cluster_dims__(2, 1, 1) __launch_bounds__(384, 1)
k_gemm(const __grid_constant__ GemmMaps maps, const bf16* __restrict__ x, bf16* __restrict__ out) {
  extern __shared__ __align__(1024) unsigned char smem_raw[];
  const uint32_t sb = smem_u32(smem_raw);
  const int tid = threadIdx.x, wid = __shfl_sync(~0u, tid >> 5, 0), wg = wid >> 2, w = wid & 3, lane = tid & 31;
  const int rank = blockIdx.x & 1, cl = blockIdx.x >> 1;
  const uint32_t bFull = sb + G_BAR, bEmpty = bFull + 32, bPub = bFull + 64, dFull = bFull + 72, dEmpty = dFull + 48, dW = dEmpty + 48, dReady = dW + 8,
                 xF = bFull + 256, xE = xF + 64;
  const int dq = blockIdx.x & 3;
  if (tid >= 32 && tid < 32 + 21) asm volatile("prefetch.tensormap [%0];" ::"l"(&maps.a[0] + (tid - 32)) : "memory");
  if (tid == 0) {
    TG(95, 0);
    if (sb & 1023) __trap();
    for (int i = 0; i < G_STAGES; i++) { mbar_init(bFull + i * 8, 1); mbar_init(bEmpty + i * 8, 4); }
    for (int i = 0; i < D_STAGES; i++) { mbar_init(dFull + i * 8, 1); mbar_init(dEmpty + i * 8, 2); }
    for (int i = 0; i < 16; i++) mbar_init(xF + i * 8, 1);
    mbar_init(dW, 1);
    mbar_init(bPub, 8);
    sts_u1(dReady, 0);
    asm volatile("fence.mbarrier_init.release.cluster;" ::: "memory");
  }
  __syncthreads();
  asm volatile("barrier.cluster.arrive.relaxed.aligned;" ::: "memory");
  if (wg == 2) {
    asm volatile("setmaxnreg.dec.sync.aligned.u32 40;");
    asm volatile("barrier.cluster.wait.aligned;" ::: "memory");
    if (w == 0 && lane == 0) {
      int st = 0, ph = 1, pe = 0, pcol = 0, pmt = 0;
#define ELOAD(j)                                                                           \
  {                                                                                        \
    mbar_wait(bEmpty + st * 8, ph);                                                        \
    const uint32_t full = bFull + st * 8, sa = sb + st * G_STAGE_BYTES;                    \
    mbar_expect_tx(full, (pe - 2) * 16384);                                                \
    tma_load_2d(sa, &maps.e[pe * 2 - 5], pcol + (j) * 64, pmt * 128, full);                \
    if (pe == T_WO) tma_load_2d(sa + 16384, &maps.e[2], pcol + (j) * 64, pmt * 128, full); \
    if (++st == G_STAGES) { st = 0; ph ^= 1; }                                             \
  }
      for (int r = 0;; r++) {
        const Tile t = decode(c_list[cl][r]);
        if (!t.valid) break;
        const int mt = t.mp * 2 + rank;
        const CUtensorMap *am = &maps.a[t.ty], *bm = &maps.b[t.ty];
        if (r == 0) {
          for (int kb = 0; kb < G_STAGES; kb++) {
            mbar_expect_tx(bFull + kb * 8, G_STAGE_BYTES);
            load_b(sb + kb * G_STAGE_BYTES + 16384 + rank * 16384, bm, kb * 64, t.nt * 4 + rank * 2, bFull + kb * 8);
          }
        }
        if (t.ty == T_W1) wait_cnt(C_LN, 96);
        else if (t.ty == T_W2) { wait_cnt(C_H1 + mt, 4); if (mt > 0) wait_cnt(C_H1 + mt - 1, 4); if (mt < 15) wait_cnt(C_H1 + mt + 1, 4); }
        else if (t.ty == T_W3) wait_cnt(C_LN1 + mt, 4);
        else if (t.ty == T_W4) wait_cnt(C_H3 + mt, 14);
        else wait_cnt(C_OX + mt * 4 + 3, 128);
        if (pe == T_WO) wait_cnt(C_G + pmt, 4);
        fence_async_all();
        TG(r, 0);
        if (r == 0 && cl == 0) ST(5);
        for (int kb = 0; kb < t.nkb; kb++) {
          const bool early = r == 0 && kb < G_STAGES;
          if (pe && !(kb & ~12)) ELOAD(kb >> 2);
          if (kb >> 2 == 12) tma_prefetch_2d(&maps.e[t.ty * 2 - 5], t.nt * 256 + (kb & 3) * 64, mt * 128);
          mbar_wait(bEmpty + st * 8, ph);
          const uint32_t full = bFull + st * 8, sa = sb + st * G_STAGE_BYTES;
          if (!early) mbar_expect_tx(full, G_STAGE_BYTES);
          int roff = 0;
          if (t.ty == T_W2) { int gq = kb >> 2; roff = (gq & 1) ? (gq >> 1) + 1 : -((gq >> 1) + 1); }
          tma_load_2d(sa, am, kb * 64, mt * 128 + roff, full);
          if (!early) load_b(sa + 16384 + rank * 16384, bm, kb * 64, t.nt * 4 + rank * 2, full);
          if (++st == G_STAGES) { st = 0; ph ^= 1; }
        }
        pe = t.ty >= T_W4 ? t.ty : 0; pcol = t.nt * 256; pmt = mt;
        if (pe && t.flush) {
          if (pe == T_WO) { wait_cnt(C_G + mt, 4); fence_async_all(); }
          for (int j = 0; j < 4; j++) ELOAD(j);
          pe = 0;
        }
        for (int i = 0; i < (t.ty == T_W2 ? 2 : 0); i++) {
          mbar_wait(bEmpty + st * 8, ph);
          const uint32_t full = bFull + st * 8, sa = sb + st * G_STAGE_BYTES;
          mbar_expect_tx(full, 32768);
          tma_load_2d(sa, &maps.e[0], pcol + i * 128, mt * 128, full);
          tma_load_2d(sa + 16384, &maps.e[0], pcol + i * 128 + 64, mt * 128, full);
          if (++st == G_STAGES) { st = 0; ph ^= 1; }
        }
      }
      if (c_list[cl][23] < NSEG) {
        for (int i = 0; i < G_STAGES; i++) {
          mbar_wait(bEmpty + st * 8, ph);
          if (++st == G_STAGES) { st = 0; ph ^= 1; }
        }
        for (int i = 0; i < D_STAGES; i++) {
          mbar_expect_tx(dFull + i * 8, 16384);
          tma_load_3d(sb + D_RING + i * 16384, &maps.b[T_WO], 0, dq * 1024 + i * 64, cl & ~1, dFull + i * 8);
        }
        mbar_expect_tx(dW, D_RING);
        for (int q = 0; q < 2 * (8 - NRD); q++) tma_load_3d(sb + D_W + q * 16384, &maps.b[T_WO], 0, dq * 1024 + NRD * 128 + q * 64, cl & ~1, dW);
      }
    } else if (w == 3 && lane == 0) {
      int ph = 0;
      for (int r = 0;; r++) {
        const Tile t = decode(c_list[cl][r]);
        if (!t.valid) break;
        if (t.ty != T_WO) { mbar_wait_long(bPub, ph); ph ^= 1; sig_cnt(t.ty * 16 + t.mp * 2 + rank); TG(r, 3); }
      }
    }
    __syncwarp();
    if (w < 3) bar_sync(3, 96);
    const int s0 = c_list[cl][23];
    if (!(w & 1) && lane == 0 && s0 < NSEG) {
      int st = w >> 1, ph = 0, ready = s0;
      for (int i = D_STAGES + st; i < 2 * NRD + 4 * (NSEG - s0); i += 2) {
        const int n = i - 2 * NRD, s = s0 + (n >> 3) * 2 + 1;
        if (s >= ready) {
#pragma unroll 1
          for (int it = 0; s >= ready && it < 64 * WAIT_LIM; it++)
            asm volatile("ld.acquire.cta.shared.u32 %0, [%1];" : "=r"(ready) : "r"(dReady) : "memory");
          fence_async_all();
          TG(24 + s, 0);
        }
        mbar_wait(dEmpty + st * 8, ph);
        const uint32_t full = dFull + st * 8, sa = sb + D_RING + st * 16384;
        if ((s | 2) == 51) TG(40 + (n & 7), s & 2);
        mbar_expect_tx(full, 16384);
        if (n < 0) tma_load_3d(sa, &maps.b[T_WO], 0, dq * 1024 + i * 64, cl & ~1, full);
        else tma_load_3d(sa, &maps.od, 0, s * 32 - 32, dq * 16 + d_head(n & 7) * 2, full);
        if ((st += 2) >= D_STAGES) { st -= D_STAGES; ph ^= 1; }
      }
    } else if (w == 1) {
      int ready = s0;
#pragma unroll 1
      for (int it = 0; ready < NSEG; it++) {
        const int q = min(ready + (lane & 7), NSEG - 1);
        const bool ok = (lane < 16 && ld_acq(lane < 8 ? C_OX + q : C_G + (q >> 2)) >= (lane < 8 ? 128 : 4)) || it > WAIT_LIM;
        const uint32_t m = __ballot_sync(~0u, ok);
        const int n = __ffs(~(m & (m >> 8) & 255)) - 1;
        ready = min(ready + n, NSEG);
        __syncwarp();
        if (n == 0) __nanosleep(NSLP);
        else if (lane == 0) asm volatile("st.release.cta.shared.u32 [%0], %1;" ::"r"(dReady), "r"(ready) : "memory");
      }
      uint32_t last = 0;
      if (lane == 0) asm volatile("atom.acq_rel.gpu.global.inc.u32 %0, [%1], %2;" : "=r"(last) : "l"(g_cnt + C_DONE * 8), "r"(gridDim.x - 1) : "memory");
      if (__shfl_sync(~0u, last, 0) == gridDim.x - 1)
        for (int i = lane; i < C_DONE; i += 32) g_cnt[i * 8] = 0;
    }
    __syncwarp();
  } else {
    asm volatile("setmaxnreg.inc.sync.aligned.u32 232;");
    asm volatile("barrier.cluster.wait.aligned;" ::: "memory");
    const bool leader = (tid & 127) == 0;
    bool pubq = false;
    {
      const int rr = (lane & 7) + ((lane >> 3) & 1) * 8;
      const uint32_t sb = __shfl_sync(~0u, smem_u32(smem_raw), 0), bFull = sb + G_BAR, bEmpty = bFull + 32, bPub = bFull + 64;
      const uint32_t xo = __shfl_sync(~0u, rr * 128 + (((lane >> 4) ^ (rr & 7)) << 4), lane), buf = sb + G_STG + wid * 4096, erow = wid * 2048;
      int st = 0, ph = 0, r = 0, tv = c_list[cl][0];
      uint32_t pk[64];
      int dact = -1, ecol = 0, drow = 0, done = 0, prev = 0;
      bool hold = false, flush = false, fast = false;
      const CUtensorMap* dcm = nullptr;
      float acc[128];
      if (PP && wg) bar_arrive(4, 256);
      while (true) {
        const Tile t = decode(tv);
        const int mt = t.mp * 2 + rank;
        const bool run = t.valid && !hold;
#define KBLOCK(kb)                                                                                      \
  {                                                                                                     \
    mbar_wait(bFull + st * 8, ph);                                                                      \
    uint32_t sa = sb + st * G_STAGE_BYTES;                                                              \
    uint64_t da = make_desc(sa + wg * 8192, 16, 1024, 1), db = make_desc(sa + 16384, 8192, 1024, 1);    \
    if (PP) bar_sync(4 + wg, 256);                                                                      \
    WG_FENCE();                                                                                         \
    _Pragma("unroll") for (int k = 0; k < 4; k++) {                                                     \
      wgmma_n256(acc, da + k * 2, db + k * 128, ((kb) | k) != 0);                                       \
      if (k == PP - 1) bar_arrive(5 - wg, 256);                                                         \
    }                                                                                                   \
    WG_COMMIT();                                                                                        \
    if ((kb) > 0) { WG_WAIT(1); if (leader) arrive_both(bEmpty + prev * 8); }                           \
    prev = st;                                                                                          \
    if (++st == G_STAGES) { st = 0; ph ^= 1; }                                                          \
  }
#define PUBLISH()                                                                                       \
  {                                                                                                     \
    if (lane == 0) { asm volatile("cp.async.bulk.wait_group 0;" ::: "memory"); if (pubq) mbar_arrive(bPub); } \
    __syncwarp();                                                                                       \
    pubq = false;                                                                                       \
  }
#define EAPPLY(p, eb, OP)                                                                  \
  _Pragma("unroll") for (int q = 0; q < 4; q++) {                                          \
    uint32_t a[4];                                                                         \
    ldsm4(a, (eb) + (xo ^ (q << 5)));                                                      \
    _Pragma("unroll") for (int i = 0; i < 4; i++) (p)[q * 4 + i] = OP((p)[q * 4 + i], a[i]); \
  }
#define ADDH(a, b) fma2(a, dact == T_WO ? 0x3F803F80u : 0x3F003F00u, b)
        const bool eop = dact == T_W4 || dact == T_WO;
        const bool slow = run && !fast;
#pragma unroll
        for (int c = 0; c < 4; c++) {
          const int es = st, eph = ph;
          if (eop && ++st == G_STAGES) { st = 0; ph ^= 1; }
          if (run) KBLOCK(c ? c : done);
          if (run && c == 0 && tid == 0 && !done) TG(r, 1);
          if (eop) {
            mbar_wait(bFull + es * 8, eph);
            const uint32_t eb = sb + es * G_STAGE_BYTES + erow;
            if (dact == T_WO) EAPPLY(pk + c * 16, eb + 16384, mul2);
            EAPPLY(pk + c * 16, eb, ADDH);
            bar_sync(1 + wg, 128);
            if (leader) arrive_both(bEmpty + es * 8);
          }
          activate<NA0>(pk + c * 16, dact);
          if (slow) KBLOCK(1);
          activate<NA1 - NA0>(pk + c * 16 + NA0, dact);
          if (run) KBLOCK(1);
          activate<16 - NA1>(pk + c * 16 + NA1, dact);
          if (slow) KBLOCK(1);
          if (c == 0 && pubq) PUBLISH();
          if (dact >= 0) epi_store(pk + c * 16, buf + (c & 1) * 2048, xo, dcm, ecol + c * 64, drow, lane);
        }
        if (run) done += slow ? 16 : 8;
        if (dact == T_W2) {
          const uint2* sp = g_rstat + (drow + (lane >> 2)) * 4 + (lane & 3);
          uint2 q[2];
          for (int n = 0; n < WAIT_LIM; n++) {
            q[0] = ld_rlx2(sp); q[1] = ld_rlx2(sp + 32);
            if (!__any_sync(~0u, q[0].y == 0u || q[1].y == 0u)) break;
          }
          uint32_t nmb[2], hi[2], lo[2];
#pragma unroll
          for (int e = 0; e < 2; e++) {
            const float sp = __uint_as_float(q[e].x);
            float a = sp + __shfl_xor_sync(~0u, sp, 1);
            a += __shfl_xor_sync(~0u, a, 2);
            const float mean = a * (1.f / 1024.f), dm = sp * (1.f / 256.f) - mean;
            float v = fmaf(256.f * dm, dm, __uint_as_float(q[e].y & 0x7fffffffu));
            v += __shfl_xor_sync(~0u, v, 1);
            v += __shfl_xor_sync(~0u, v, 2);
            nmb[e] = pack_bf16(-mean, -mean);
            split2(ln_inv(v), hi[e], lo[e]);
          }
#pragma unroll
          for (int i = 0; i < 64; i++) pk[i] = scale2(add2(pk[i], nmb[i & 1]), hi[i & 1], lo[i & 1]);
          dact = T_LN;
          dcm = &maps.c[5];
          hold = flush;
          continue;
        }
        pubq = dact >= 0 && dact != T_WO;
        dact = -1;
        if (!run) {
          WG_WAIT(0);
          if (!t.valid) break;
          PUBLISH();
          hold = false;
          continue;
        }
        uint2* sp = g_rstat + (mt * 128 + wid * 16 + (lane >> 2)) * 4 + t.nt;
        if (t.ty == T_W4 && (lane & 3) == 0) { st_rlx2(sp, 0, 0); st_rlx2(sp + 32, 0, 0); }
        dact = t.ty; ecol = t.nt * 256; drow = mt * 128 + wid * 16; dcm = &maps.c[t.ty];
        flush = t.flush & 1; fast = t.flush || t.ty == T_W2; hold = flush || (t.flush && t.ty == T_W2);
        tv = c_list[cl][++r];
#pragma unroll 1
        for (int kb = done; kb < t.nkb; kb++) {
          KBLOCK(1);
          if (kb == done + 1 && pubq) PUBLISH();
        }
        WG_WAIT(0);
        if (leader) arrive_both(bEmpty + prev * 8);
        if (tid == 0) TG(r - 1, 2);
#pragma unroll
        for (int i = 0; i < 64; i++) pk[i] = pack_bf16(acc[2 * i], acc[2 * i + 1]);
        done = 0;
        if (dact == T_W2) {
#pragma unroll
          for (int h = 0; h < 2; h++) {
            mbar_wait(bFull + st * 8, ph);
            const uint32_t eb = sb + st * G_STAGE_BYTES + erow;
            EAPPLY(pk + h * 32, eb, ADDH);
            EAPPLY(pk + h * 32 + 16, eb + 16384, ADDH);
            bar_sync(1 + wg, 128);
            if (leader) arrive_both(bEmpty + st * 8);
            if (++st == G_STAGES) { st = 0; ph ^= 1; }
          }
          const uint32_t one = 0x3F803F80u;
          float *sm = acc, *s2 = acc + 4, *q0 = acc + 8, *q1 = acc + 12;
#pragma unroll
          for (int i = 0; i < 32; i++) acc[i] = 0.f;
#pragma unroll
          for (int i = 0; i < 64; i += 4) mma16816((i & 4) ? s2 : sm, pk[i], pk[i + 1], pk[i + 2], pk[i + 3], one, one);
          sm[0] += s2[0]; sm[2] += s2[2];
          const uint32_t c0 = pack_bf16(sm[0] * (-1.f / 256.f), sm[0] * (-1.f / 256.f)), c1 = pack_bf16(sm[2] * (-1.f / 256.f), sm[2] * (-1.f / 256.f));
#pragma unroll
          for (int i = 0; i < 64; i += 4) {
            const uint32_t a0 = add2(pk[i], c0), a1 = add2(pk[i + 1], c1), a2 = add2(pk[i + 2], c0), a3 = add2(pk[i + 3], c1);
            mma16816(q0, a0, a1, a2, a3, a0, a2);
            mma16816(q1, a0, a1, a2, a3, a1, a3);
          }
          if ((lane >> 3) == (lane & 3)) {
            const float e0 = fmaf(sm[0], 1.f / 256.f, bf_lo(c0)), e1 = fmaf(sm[2], 1.f / 256.f, bf_lo(c1));
            const float m0 = fmaxf(fmaf(-256.f * e0, e0, (lane & 4) ? q0[1] : q0[0]), 0.f);
            const float m1 = fmaxf(fmaf(-256.f * e1, e1, (lane & 4) ? q1[3] : q1[2]), 0.f);
            st_rlx2(sp, __float_as_uint(sm[0]), __float_as_uint(m0) | 0x80000000u);
            st_rlx2(sp + 32, __float_as_uint(sm[2]), __float_as_uint(m1) | 0x80000000u);
          }
          __syncwarp();
        }
      }
    }
    if (tid == 0) { TG(95, 1); ST(8 + cl); }
    const int s0 = c_list[cl][23];
    if (s0 < NSEG) {
      uint32_t W[NRD * 8][4];
      const uint32_t peer = peer_base(sb, rank ^ 1);
#define XFREE() if (lane == 0) { mbar_expect_tx(xF + wid * 8, 2048); arrive_remote(xE + wid * 8 + peer); }
      int st = 0, ph = 0;
      const uint32_t xw = sb + D_RING + wg * 8192 + ((lane >> 4) * 8 + (lane & 7)) * 128 + (((w * 2 + ((lane >> 3) & 1)) ^ (lane & 7)) << 4);
#pragma unroll
      for (int i = 0; i < 2 * NRD; i++) {
        mbar_wait(dFull + st * 8, ph);
#pragma unroll
        for (int k = 0; k < 4; k++) ldsm4t(W[i * 4 + k], xw + st * 16384 + k * 2048);
        bar_sync(1 + wg, 128);
        if (leader) mbar_arrive(dEmpty + st * 8);
        if (++st == D_STAGES) { st = 0; ph ^= 1; }
      }
      PUBLISH();
      XFREE();
      mbar_wait(dW, 0);
      if (tid == 0) TG(95, 2);
      const uint32_t in = sb + G_STG + wid * 4096 + lane * 16, mine = (cl & 1) * 1024, keep = D_SUM - G_STG - wid * 2048;
      uint32_t dA = (uint32_t)make_desc(sb + D_W + wg * 8192, 1024, 1024, 1);
      const uint32_t dB = (uint32_t)make_desc(sb + D_RING, 16, 1024, 1);
      const uint32_t eb = (dq * 16 + (lane >> 2)) * D_ + (cl >> 1) * 128 + wid * 16 + (lane & 3) * 2, xb = blockIdx.x * 8192 + tid;
      int pend = 0, fin = 0;
#define SUM_LD(j) { a = lds_f4(in + (mine ^ (1024 - ((j) >> 1) * 1024)) + ((j) & 1) * 512); b = lds_f4(in + (mine ^ (1024 - ((j) >> 1) * 1024)) + ((j) & 1) * 512 + 2048); }
#define SUM_ST(j, on, u)                                                                                    \
  {                                                                                                      \
    const float c[4] = {a.x + b.x, a.y + b.y, a.z + b.z, a.w + b.w};                                     \
    if ((j) < 2)                                                                                         \
      asm volatile("{.reg .pred p; .reg .b128 r; setp.ne.b32 p, %5, 0; mov.b128 r, {%1,%2,%3,%4}; @p st.relaxed.gpu.global.b128 [%0], r;}" \
                   ::"l"(g_dx + (xb ^ 16384) + ((u) & 31) * 256 + (j) * 256), "r"(nz(asu(c[0]))), "r"(asu(c[1])), "r"(asu(c[2])), "r"(asu(c[3])), "r"(on) : "memory"); \
    else if (on) sts_f4(in + keep + ((u) & 2) * 512 + ((j) & 1) * 512, c);                                                 \
  }
#define OPERANDS(t, e)                                                                                   \
  {                                                                                                      \
    e[0] = ld_rlx1(g_gate + eo + t * 8 * D_); e[1] = ld_rlx1(g_gate + eo + t * 8 * D_ + 8);              \
    e[2] = __ldg((const uint32_t*)(x + eo + t * 8 * D_)); e[3] = __ldg((const uint32_t*)(x + eo + t * 8 * D_ + 8)); \
  }
#define RECV() { r = ld_rlx4(g_dx + xo); q = ld_rlx4(g_dx + xo + 256); }
#define CHECK() { for (int n = 0; (r.x == 0u || q.x == 0u) && n < WAIT_LIM; n++) RECV(); __syncwarp(); }
#define FIN_LD(on)                                                                                       \
  {                                                                                                      \
    if (on) { st_rlx4(g_dx + xo, 0, 0, 0, 0); st_rlx4(g_dx + xo + 256, 0, 0, 0, 0); }                    \
    a = lds_f4(in + keep + (u & 2) * 512); b = lds_f4(in + keep + (u & 2) * 512 + 512);                                                  \
  }
#define FIN_T(r, a)                                                                                      \
  {                                                                                                      \
    r.x = pack_bf16(a.x + asf(r.x), a.y + asf(r.y)); r.y = pack_bf16(a.z + asf(r.z), a.w + asf(r.w));    \
    asm volatile("movmatrix.sync.aligned.m8n8.trans.b16 %0, %0;" : "+r"(r.x));                           \
    asm volatile("movmatrix.sync.aligned.m8n8.trans.b16 %0, %0;" : "+r"(r.y));                           \
  }
#define FIN_ST(t, e, r, on)                                                                              \
  {                                                                                                      \
    const uint32_t y = add2(mul2(r.x, e[0]), e[2]), z = add2(mul2(r.y, e[1]), e[3]);                     \
    if (on) asm volatile("st.global.b32 [%0+%3], %1; st.global.b32 [%0+%4], %2;" ::"l"(out + eo), "r"(y), "r"(z), "n"(t * 16 * D_), "n"(t * 16 * D_ + 16) : "memory"); \
  }
#pragma unroll 1
      for (int s = s0; s < NSEG; s += 2) {
        float d[32];
        uint32_t e[4], f[4];
        uint4 r, q;
        float4 a, b;
        int prev = 0;
        const uint32_t par = (s >> 1) & 1;
        int u = s - 2 - 2 * pend;
#define eo (eb + u * 32 * D_)
#define xo (xb + (u & 31) * 256)
#pragma unroll
        for (int i = 0; i < 8; i++) {
          mbar_wait(dFull + st * 8, ph);
          if (leader && (s | 2) == 50) TG(24 + wg * 8 + i, s & 2);
          const uint32_t db = dB + st * 1024;
          asm volatile("" : "+r"(dA));
          WG_FENCE();
#pragma unroll
          for (int k = 0; k < 8; k++) {
            const int h = d_head(i), bo = (k >> 2) * 512 + (k & 3) * 2;
            if (h < NRD) wgmma_rs64(d, W[h < NRD ? h * 8 + k : 0], DSC(db + bo), (i | k) != 0);
            else wgmma_ss64(d, DSC(dA + ((h - NRD) * 2 + (k >> 2)) * 1024 + (k & 3) * 128), DSC(db + bo));
            if (i == DPS && !(k & 1)) { if (k) SUM_ST(k / 2 - 1, pend, s - 2); SUM_LD(k / 2); }
            if (i == DP0) { if (k == 0) OPERANDS(0, e); if (k == 2) OPERANDS(1, f); if (k == DPK) RECV(); }
            if (i == 7) {
              if (k == 0) FIN_LD(fin);
              if (k == 2) { FIN_T(r, a); FIN_T(q, b); }
              if (k == 4) FIN_ST(0, e, r, fin);
              if (k == 5) FIN_ST(1, f, q, fin);
            }
          }
          WG_COMMIT();
          if (leader && (s | 2) == 50) TG(24 + wg * 8 + i, 1 + (s & 2));
          if (i == DPS) { SUM_ST(3, pend, s - 2); if (pend) XFREE(); }
          if (i > 0) { WG_WAIT(1); if (leader) mbar_arrive(dEmpty + prev * 8); }
          if (i == DPS - 1 && pend) mbar_wait(xF + wid * 8, par ^ 1);
          if (i == 6 && fin) CHECK();
          if (i == 2) asm volatile("prefetch.global.L2 [%0];" ::"l"(((lane & 1) ? x : g_gate) + eb + (s * 32 + (lane & 2) * 4) * D_));
          prev = st;
          if (++st == D_STAGES) { st = 0; ph ^= 1; }
        }
        fin = pend;
        asm volatile("{.reg .pred p, g; ld.volatile.shared.u32 %0, [%1]; setp.gt.s32 p, %0, %2; setp.eq.b32 g, %3, 0;\n"
                     "@g barrier.red.and.aligned.pred p, 1, 128, p; @!g barrier.red.and.aligned.pred p, 2, 128, p; selp.b32 %0, 1, 0, p;}"
                     : "=&r"(pend) : "r"(dReady), "r"(s + 3), "r"(wg) : "memory");
        mbar_wait(xE + wid * 8, par);
        WG_WAIT(0);
        asm volatile("" : D16(d));
        asm volatile("" : D16((d + 16)));
        if (leader) mbar_arrive(dEmpty + prev * 8);
#pragma unroll
        for (int j = 0; j < 8; j++) {
          const uint32_t a = in + (j >> 2) * 1024 + ((j) & 1) * 512;
          if ((((j) >> 1) & 1) == rank) sts_f4(a, d + 4 * j);
          else sta4(a + 2048 + peer, make_uint4(asu(d[4 * j]), asu(d[4 * j + 1]), asu(d[4 * j + 2]), asu(d[4 * j + 3])), xF + wid * 8 + peer);
        }
        if (tid == 0) TG(24 + s, 1);
        if (!pend) {
          u = s - 2 * fin;
          OPERANDS(0, e);
          OPERANDS(1, f);
          RECV();
          mbar_wait(xF + wid * 8, par);
#pragma unroll
          for (int j = 0; j < 4; j++) { SUM_LD(j); SUM_ST(j, 1, s); }
          if (s + 2 < NSEG) XFREE();
#pragma unroll 1
          while (u < s || s + 2 == NSEG) {
            CHECK();
            FIN_LD(true);
            FIN_T(r, a);
            FIN_T(q, b);
            FIN_ST(0, e, r, true);
            FIN_ST(1, f, q, true);
            if (u == s || s + 2 < NSEG) break;
            u = s;
            OPERANDS(0, e);
            OPERANDS(1, f);
            RECV();
          }
          fin = 1;
        }
      }
    }
    else PUBLISH();
    if (PP && !wg) bar_sync(4, 256);
#undef eo
#undef xo
    if (tid == 0) { TG(95, 3); ST(32 + cl); }
  }
  asm volatile("barrier.cluster.arrive.relaxed.aligned; barrier.cluster.wait.aligned;" ::: "memory");
}
struct RecMaps { CUtensorMap w[3], wb[3], wo, xn, xn1, xn2, ox; };
#define NR1 13
#define NLOW 5
constexpr int R_WS = 0, R_WO = 2 * (32 - NR1) * 2048, R_Q = R_WO + 81920, R_K = R_Q + 6144, R_G1 = R_K + 6144,
              R_XN = R_WO + 98304, R_MEM = R_XN + 16384, R_VX = R_MEM + 16384, R_VM = R_VX + 8192, R_O = R_VM + 4096,
              R_TS = R_O + 4096, R_SC = R_TS + 5120, R_BAR = R_SC + 1280, R_TAB = R_BAR + 256, R_SMEM = R_TAB + 128;
constexpr int STG = R_SC - 2 * (32 + NR1) * 2048, NDIR = STG / 2048;
__device__ constexpr int stg(int g, int i) { return STG + (i == 0 ? 131072 + g * NR1 * 2048 : (i == 1 ? g * 98304 : 32768 + g * 32768)); }
static_assert(R_SMEM <= 232448 && R_G1 + 2048 <= R_XN && STG % 1024 == 0 && R_WO <= STG + 32768 && R_XN >= STG + 98304, "smem");
constexpr uint32_t SB = 1024;
constexpr int POLL_LIM = 1 << 20;
enum { BAR_MEM = 1, BAR_RED, BAR_O, BAR_BG, BAR_C, BAR_G1, BAR_X, BAR_H, BAR_ST };
#define bC (sb + R_BAR)
#define bX (bC + 48)
#define bWS (bC + 128)
#define bWo (bC + 136)
#define bM (bC + 144)
#define bS (bC + 152)
#define bTs (bC + 176)
#define bIn (bC + 184)
#define bTok (bC + 192)
#define aInfo (bC + 200)
#define aCal (bC + 224)
constexpr int XC_G2N = 256, XC_PRB = 384, XC_T = 386;
#define TINIT 6200, 1050, 200, 300, 400
__constant__ int c_tune[16] = {TINIT};
#define T_STEP c_tune[0]
#define T_G2 c_tune[1]
#define D_G1 c_tune[2]
#define D_G2 c_tune[3]
#define T_REL c_tune[4]
#define NWF 2
#define NBF 2
#define NCH 1
#define PAT 1
#define INSM(k) ((k) % 5 % 2 == 0)
#define SIDX(k) ((k) / 5 * 3 + ((k) % 5 + 1) / 2)
#define RIDX(k) (INSM(k) ? 0 : (k) - SIDX(k))
#define NEA0 3
#define NEA1 3
#define NEB 2
#define HOLE0 6
#define HOLE1 6
#define GST 0
#define THR 0
#define LEAD 15
#define WOT 2
#define WOW 1
#define XPOS 0
#define NPRB 3
#define PFX 2

__device__ __forceinline__ void xn_pair(const CUtensorMap* m, uint32_t dst, uint32_t bar, int bytes, int n, int c, int half) {
  mbar_expect_tx(bar, bytes);
  asm volatile(
      "cp.async.bulk.tensor.4d.shared::cluster.global.mbarrier::complete_tx::bytes [%0], [%1, {%3, %4, %5, %6}], [%2];"
      ::"r"(dst), "l"(m), "r"(bar), "r"(0), "r"(n * 32), "r"(c), "r"(half) : "memory");
}

__global__ void __launch_bounds__(384, 1)
k_rec(const __grid_constant__ RecMaps maps, const bf16* __restrict__ x, const bf16* __restrict__ mem0, unsigned char* xch) {
  extern __shared__ __align__(1024) unsigned char smem_raw[];
  const uint32_t sb = smem_u32(smem_raw);
  if ((sb & 0xffffff) != SB) __trap();
  const int tid = threadIdx.x, wid = __shfl_sync(~0u, tid >> 5, 0), wg = wid >> 2, w = wid & 3;
  const int lane = tid & 31;
  const int cta = blockIdx.x, h = cta / 3, j = cta - h * 3, cl = h >> 1, r0 = (h & 1) * 3;
  const bool isA = j < 2;
  if (tid >= 32 && tid < 32 + 11) asm volatile("prefetch.tensormap [%0];" ::"l"(&maps.w[0] + (tid - 32)) : "memory");
  if (tid == 0 && cta == 0) ST(2);
  asm volatile("griddepcontrol.launch_dependents;" ::: "memory");
  uint32_t u[3][16] = {};
  const int row = min((cta * 8 + wid) * 3, S_ - 3);
  if (wg < 2) {
#pragma unroll
    for (int i = 0; i < 3; i++) row_ld(u[i], x + (size_t)(row + i) * D_, lane);
  }
  if (tid == 0) {
    for (int i = 0; i < 18; i++) mbar_init(bC + i * 8, 1);
    mbar_init(bM, 2); mbar_init(bS, 1); mbar_init(bTs, 1); mbar_init(bIn, 2); mbar_init(bTok, 4);
    asm volatile("fence.mbarrier_init.release.cluster;" ::: "memory");
  }
  if ((wid >> 1) != 4) {
    bar_sync(BAR_G1, 384);
#pragma unroll 1
    for (int pass = wg >> 1; pass < 2; pass++) {
      bf16* dst = (pass ? g_xn2 : g_xn) + (size_t)row * D_;
      if (pass == 0) {
        if (__any_sync(~0u, after(c_tune[15], u[0][15] ^ u[1][15] ^ u[2][15], c_tune[15]))) __trap();
        bar_arrive(BAR_X, 320);
        if (tid == 0) TG(1, 0);
      }
#pragma unroll
      for (int i = 0; i < 3; i++) ln_packed(u[i]);
      if (wg < 2 && (cta * 8 + wid) * 3 < S_) {
#pragma unroll
        for (int i = 0; i < 3; i++) row_st(u[i], dst + i * D_, lane);
      }
    }
  } else {
    bar_arrive(BAR_G1, 384);
    uint4* z = (uint4*)(xch + (isA ? (h * 2 + j) * 4 : XC_G2N + ((h >> 3) & 1) * 48 + (h >> 4) * 64 + ((h >> 1) & 3) * 4 + (h & 1)) * 4096);
#pragma unroll 4
    for (int i = 0; i < (isA ? 16 : 4); i++) z[i * 64 + (tid & 63)] = make_uint4(0, 0, 0, 0);
    if (cta == cl * 6) {
      uint32_t* p = (uint32_t*)(xch + (XC_PRB + w) * 4096 + cl * 128);
      st_rlx1(p + lane, 0);
      uint32_t lat = ~0u;
#pragma unroll 1
      for (int r = 0; r < NPRB && lane == 0; r++) {
        uint32_t v, c0 = clk32();
        asm volatile("atom.relaxed.gpu.global.add.u32 %0, [%1], 1;" : "=r"(v) : "l"(p) : "memory");
        if (v >> 30) break;
        lat = min(lat, clk32() - c0);
      }
      if (lane == 0) { sts_u1(aInfo + w * 4, lat); TG(3, w); }
      __syncwarp();
    }
  }
  asm volatile("barrier.cluster.arrive.relaxed.aligned;" ::: "memory");
#define WMAP(g) (&maps.w[isA ? (g) : 2])
#define WCOL(g) (h * 128 + (isA ? j : (g)) * 64)
  const uint32_t xlo = (uint32_t)(uint64_t)xch, xhi = (uint32_t)((uint64_t)xch >> 32);
#define XP(off) xptr(xlo + (off), xhi)
  if (wg < 2) {
    fence_async_all();
    if (tid == 0) TG(1, 1);
    if (wid != 7) bar_arrive(BAR_C, 256);
    else bar_sync(BAR_C, 256);
    if (tid == 224) { sig_cnt(C_LN); TG(0, 1); }
    __syncwarp();
    if (wid == 7) bar_arrive(BAR_BG, 96);
    asm volatile("setmaxnreg.inc.sync.aligned.u32 224;");
    const uint32_t l16c = opaque(sb + lane * 16);
    const uint32_t xwc = opaque(sb + ((lane >> 4) * 8 + (lane & 7)) * 128 + (((w * 2 + ((lane >> 3) & 1)) ^ (lane & 7)) << 4));
    uint32_t W0[32][4], W1[NR1][4];
#pragma unroll
    for (int i = 0; i < 3; i++) {
      mbar_wait(bC + (wg * 3 + i) * 8, 0);
      if (i == 0 && tid == 0) TG(1, 2);
#pragma unroll
      for (int k = 0; k < (i ? 16 : NR1); k++) ldsm4t(i ? W0[i ? i * 16 - 16 + k : 0] : W1[i ? 0 : k], (wg ? stg(1, i) : stg(0, i)) + k * 2048 + xwc);
      if (i) bar_arrive(i == 1 ? BAR_ST : BAR_H, 288);
    }
    if (tid == 0) TG(1, 3);
    asm volatile("barrier.cluster.wait.aligned;" ::: "memory");
    mbar_wait(bWS, 0);
    if (tid == 0) TG(0, 2);
    const uint32_t dX = (uint32_t)make_desc(SB + R_XN, 16, 1024, 1) + wg * 512, dW = (uint32_t)make_desc(SB + R_WS, 1024, 1024, 1) + wg * (32 - NR1) * 128;
    const uint32_t pB = peer_base(sb, r0 + 2);
#pragma unroll 1
    for (int s = 0; s < NSEG; s++) {
      uint32_t xw = xwc, l16 = l16c;
      asm volatile("" : "+r"(xw), "+r"(l16));
#define LANE0 ((l16 & 511) == 0)
      {
        float d0[16], d1[16];
#pragma unroll
        for (int c = 0; c < 8; c++) {
          if (c == 7 || !(c & 1)) mbar_wait(bX + (c < 4 ? c / 2 : (c == 7 ? 6 : c - 2) + wg) * 8, s & 1);
          if (c == NEB && s > 0 && !isA && wid == 7) {
            bar_sync(BAR_ST, 160);
            if (LANE0 && s > 1) sig_cnt(C_OX + s - 2, 4);
            __syncwarp();
          }
          if (c <= 3 && s > 0 && c == (isA ? (wg ? NEA1 : NEA0) : NEB)) bar_sync(BAR_BG, 384);
          if ((c == HOLE0 || c == HOLE1) && s > 0 && isA && c == (wg ? HOLE1 : HOLE0)) bar_sync(BAR_H, 384);
          const uint32_t db = dX + (c & 2) * 512 + (c & 1) * 256 + (c < 4 ? 0 : c_tune[15]);
          uint32_t tmp[4];
          if (c < NLOW) {
#pragma unroll
            for (int i = 0; i < 4; i++) asm volatile("or.b32 %0, %1, %2;" : "=r"(tmp[i]) : "r"(W0[c * 4][i]), "r"(c_tune[15]));
          }
          WG_FENCE();
#pragma unroll
          for (int kk = 0; kk < 4; kk++) {
            const int k = c * 4 + kk;
            if (c < 7) wgmma_rs32(d0, kk == 0 && c < NLOW ? tmp : W0[k], DSC(db + kk * 2), k != 0);
            if (kk == 0 && c + 1 < NLOW) WG_COMMIT();
            if (!INSM(k)) wgmma_rs32(d1, W1[RIDX(k)], DSC(db + kk * 2), k != 0);
            else wgmma_ss32(d1, DSC(dW + SIDX(k) * 128), DSC(db + kk * 2), k != 0);
          }
          WG_COMMIT();
          if (c == 7) {
#pragma unroll
            for (int kk = 0; kk < 4; kk++) wgmma_rs32(d0, W0[28 + kk], DSC(db + kk * 2), 1);
            WG_COMMIT();
          }
          const bool pause = c + 1 == (isA ? (wg ? NEA1 : NEA0) : NEB);
          if ((c == 1 || c == 2) && pause) WG_WAIT(0);
          if (c + 1 < NLOW || c == 4) WG_WAIT(1);
#pragma unroll
          for (int f = 1; f <= 3; f++) {
            if (f != c && f + 1 != c) continue;
            const bool early = f < 3 && f + 1 == (isA ? (wg ? NEA1 : NEA0) : NEB);
            if (w == 0 && LANE0 && early == (f == c)) {
              if (f == 1) {
                xn_pair(&maps.xn1, sb + R_XN + wg * 8192, bX + (2 + wg) * 8, 8192, s, 4, wg);
              } else {
                mbar_expect_tx(bX + (f * 2 + wg) * 8, 4096);
                tma_load_2d(sb + R_MEM + wg * 8192 + (f - 2) * 4096, &maps.xn, wg * 512 + (f + 4) * 64, s * 32, bX + (f * 2 + wg) * 8);
              }
            }
            __syncwarp();
          }
        }
        const uint32_t ex = l16 + R_XN + w * 2048;
        WG_WAIT(1);
        asm volatile("" : D16(d1));
#pragma unroll
        for (int i = 0; i < 4; i++) sts_f4(ex + wg * 8192 + i * 512, d1 + 4 * i);
        bar_sync(BAR_C, 256);
#pragma unroll
        for (int i = 0; i < 4; i++) {
          const float4 x = lds_f4(ex + (wg ^ 1) * 8192 + i * 512);
          d1[4 * i] = x.x; d1[4 * i + 1] = x.y; d1[4 * i + 2] = x.z; d1[4 * i + 3] = x.w;
        }
        WG_WAIT(0);
        asm volatile("" : D16(d0));
        if (w == 0 && LANE0) mbar_arrive(bM);
        if (s > 0 && tid < 32) { s--; TR(17); s++; }
        uint32_t f[8];
#pragma unroll
        for (int i = 0; i < 8; i++) f[i] = pack_bf16(d0[2 * i] + d1[2 * i], d0[2 * i + 1] + d1[2 * i + 1]);
        if (isA) {
          const uint32_t aq = l16 + (l16 & 256) * 3 + R_Q + wg * 6144 + w * 256;
          stsm4t(aq, f[0], f[1], f[2], f[3]);
          stsm4t(aq + 2048, f[4], f[5], f[6], f[7]);
        } else {
          const uint32_t av = l16 + R_VX + w * 2048 + wg * 1024;
          if (s > 0) mbar_wait(bTok, (s - 1) & 1);
          sts_u4(av, make_uint4(f[0], f[1], f[2], f[3])); sts_u4(av + 512, make_uint4(f[4], f[5], f[6], f[7]));
        }
        if (s > 0 && tid < 32) { s--; TR(18); s++; }
      }
      {
        const uint32_t aW = xw + R_WS + wg * (32 - NR1) * 2048, aMem = l16 + R_MEM + wg * 8192;
        float a[4][4];
        uint32_t b[16][4], f[32 - NR1][4], ck[14];
#define PAIR(i) (i)
#pragma unroll
        for (int i = 0; i < NWF; i++) ldsm4t(f[i], aW + i * 2048);
#pragma unroll
        for (int i = 0; i < 4; i++) a[i][0] = a[i][1] = a[i][2] = a[i][3] = 0.f;
        bar_sync(BAR_MEM, 384);
#pragma unroll
        for (int i = 0; i < NBF - 1; i++) ldsm4t(b[i], aMem + PAIR(i) * 512);
#pragma unroll
        for (int i = 0; i < 16; i++) {
          const int p = PAIR(i);
          if (i + NBF - 1 < 16) ldsm4t(b[i + NBF - 1], aMem + PAIR(i + NBF - 1) * 512);
#pragma unroll
          for (int e = 0; e < 2; e++) {
            const int k = 2 * PAIR(i > 0 ? i - 1 : 0) + e, q = SIDX(k) + NWF;
            if (i > 0 && INSM(k) && q < 32 - NR1) ldsm4t(f[q], aW + q * 2048);
          }
          if (i < 14) ck[i] = clk32();
          if (i == 1 && tid < 32) TRX(0, ck[0]);
          if (i > 1) ck[0] |= ck[i - 2];
#pragma unroll
          for (int e = 0; e < 2; e++) {
            const int k = 2 * p + e;
            const uint32_t* u = INSM(k) ? f[INSM(k) ? SIDX(k) : 0] : W1[RIDX(k)];
            mma16816(a[2 + e % NCH], u[0], u[1], u[2], u[3], b[i][2 * e], b[i][2 * e + 1]);
            mma16816(a[e % NCH], W0[k][0], W0[k][1], W0[k][2], W0[k][3], b[i][2 * e], b[i][2 * e + 1]);
          }
        }
        l16 = after(l16, ck[0], 0);
        if (NCH == 2) {
#pragma unroll
          for (int i = 0; i < 4; i++) { a[0][i] += a[1][i]; a[2][i] += a[3][i]; }
        }
        const uint4 r = make_uint4(pack_bf16(a[0][0], a[0][1]), pack_bf16(a[0][2], a[0][3]), pack_bf16(a[2][0], a[2][1]), pack_bf16(a[2][2], a[2][3]));
        if (!isA) {
          sts_u4(l16 + R_VM + wid * 512, r);
          bar_arrive(BAR_RED, 384);
          if (tid < 32) TR(1);
          if (tid == 160) TRCAL(s);
          __syncwarp();
          continue;
        }
        stsm4t((l16 & ~256u) + (((l16 >> 8) & 1) ^ wg) * 6144 + R_Q + 4096 + wg * 1024 + w * 256, r.x, r.y, r.z, r.w);
        bar_arrive(BAR_RED, 384);
        fence_async_smem();
        bar_sync(BAR_X, 352);
        if (tid < 32) TR(1);
        if (tid == 160) TRCAL(s);
        __syncwarp();
      }
      if (wg == 0) {
        float c[24];
        WG_FENCE();
#pragma unroll
        for (int i = 0; i < 4; i++) wgmma_ss48(c, make_desc(SB + R_Q + i * 256, 128, 1024, 0), make_desc(SB + R_K + i * 256, 128, 1024, 0), i != 0);
        WG_COMMIT();
        asm volatile("" : "+r"(l16));
        const uint32_t at = l16 + R_TS + w * 2560 + j * 640 + pB, au = at + 512 - (l16 & 511) / 4 * 3;
        mbar_wait(bIn, s & 1);
        WG_WAIT(0);
        asm volatile("" : D16(c), "+f"(c[16]), "+f"(c[17]), "+f"(c[18]), "+f"(c[19]), "+f"(c[20]), "+f"(c[21]), "+f"(c[22]), "+f"(c[23]));
        if (w < 2) {
#pragma unroll
          for (int r = 0; r < 2; r++) {
            const float* e = c + 2 * r;
            sta4(at + r * 1280, make_uint4(pack_bf16(e[0], e[1]), pack_bf16(e[4], e[5]), pack_bf16(e[8], e[9]), pack_bf16(e[12], e[13])), bTs + pB);
            sta1(au + r * 1280, pack_bf16(e[16] + e[20], e[17] + e[21]), bTs + pB);
          }
        }
        if (tid < 32) TR(14);
      }
    }
  } else {
    asm volatile("setmaxnreg.dec.sync.aligned.u32 56;");
    const int at = tid & 127, red = h * 2 + j;
    const int g = w & 1, slot = g * (32 - NR1) + SIDX(lane);
    if (w >= 2) {
      const bool lead = cl == LEAD;
      if (lead) bar_arrive(BAR_X, 320);
      else bar_sync(BAR_X, 320);
      if (lane < 3) mbar_expect_tx(bC + (g * 3 + lane) * 8, lane ? 32768 : NR1 * 2048);
      if (lane == 3 && g) mbar_expect_tx(bWS, R_WO);
      if (!INSM(lane)) tma_load_2d_ef(sb + stg(0, 0) + (g * NR1 + RIDX(lane)) * 2048, WMAP(g ^ 1), WCOL(g ^ 1), g * 512 + lane * 16, bC + g * 24);
      __syncwarp();
#pragma unroll 1
      for (int i = 0; i < 3; i++) {
        if (i == (lead ? 2 : XPOS)) bar_sync(BAR_BG, 96);
        if (i >= THR && !lead) mbar_wait(bC + (g * 3 + i - THR) * 8, 0);
        if (lane == 0 && i < 2) tma_load_2d_ef(sb + STG + (i ? g + 1 : g * 3) * 32768, WMAP(g) + 3, WCOL(g), g * 512 + i * 256, bC + (g * 3 + 1 + i) * 8);
        __syncwarp();
      }
      if (INSM(lane) && slot < NDIR) tma_load_2d_ef(sb + R_WS + slot * 2048, WMAP(g ^ 1), WCOL(g ^ 1), g * 512 + lane * 16, bWS);
      __syncwarp();
    }
    if (w == 3) {
      bar_sync(BAR_ST, 288);
      fence_async_smem();
      if (INSM(lane) && slot >= NDIR) tma_load_2d_ef(sb + R_WS + slot * 2048, WMAP(0), WCOL(0), 512 + lane * 16, bWS);
      __syncwarp();
      if (lane < 2) {
        wait_cnt(C_LN, gridDim.x);
        fence_async_all();
        xn_pair(&maps.xn2, sb + R_XN + lane * 16384, bX + lane * 8, 16384, 0, lane * 2, 0);
        TG(2, 1);
      }
      __syncwarp();
    }
    if (w < 2) bar_sync(BAR_RED, 64);
    if (at == 0) {
      uint32_t v = 1;
      if (cta == cl * 6) v += ((__popc((XC_PRB + (lds_u1(aInfo + 4) < lds_u1(aInfo))) & 0xb3) & 1) << cl) << 16;
      asm volatile("red.release.gpu.global.add.u32 [%0], %1;" ::"l"(g_cnt + C_CHK * 8), "r"(v) : "memory");
      int n = 0;
#pragma unroll 1
      do {
        asm volatile("ld.acquire.gpu.global.u32 %0, [%1];" : "=r"(v) : "l"(g_cnt + C_CHK * 8) : "memory");
      } while ((v & 0xffff) < gridDim.x && ++n < WAIT_LIM);
      sts_u1(aInfo + 8, v >> 16);
      TG(2, 0);
    }
    bar_sync(BAR_O, 128);
    const uint32_t pmask = __shfl_sync(~0u, lds_u1(aInfo + 8), 0), myp = (pmask >> cl) & 1;
    const int nt = isA ? 5 : 6;
    uint32_t mytile = 0;
    {
      int n = 0;
      for (int far = 1; far >= 0; far--)
        for (int i = 0; i < nt; i++) {
          const int T = j * 5 + i, p = (pmask >> T) & 1;
          if ((p ^ myp) != far) continue;
          if (n == lane) {
            mytile = T;
            sts_u1(sb + R_TAB + w * 32 + n * 4, xlo + xchunk((T * 4 + w) * 4 + (h >> 4) * 2, p) + (h & 15) * 256);
          }
          n++;
        }
    }
    if (w == 3) {
      bar_sync(BAR_H, 288);
      fence_async_smem();
      if (WOW) mbar_wait(bWS, 0);
#pragma unroll 1
      for (int i = 0; i < nt; i++) {
        if (i >= WOT) mbar_wait(bC + (i - WOT) * 8, 1);
        const bool tail = i >= nt - WOT;
        if (lane == i) {
          if (!tail || i == nt - 1) mbar_expect_tx(tail ? bWo : bC + i * 8, tail ? WOT * 16384 : 16384);
          tma_load_2d(sb + R_WO + i * 16384, &maps.wo, mytile * 64, h * 128, tail ? bWo : bC + i * 8);
        }
        __syncwarp();
      }
    }
    asm volatile("barrier.cluster.wait.aligned;" ::: "memory");
    {
      uint4 v[8];
#pragma unroll
      for (int i = 0; i < 8; i++) v[i] = __ldg((const uint4*)(mem0 + (lane >> 2) * D_ + w * 256 + i * 32 + (lane & 3) * 8));
      mbar_wait(bM, 0);
#pragma unroll
      for (int i = 0; i < 8; i++)
        stsm4t(sb + R_MEM + w * 4096 + i * 512 + (lane & 6) * 64 + (lane >> 3) * 32 + (lane & 1) * 16, v[i].x, v[i].y, v[i].z, v[i].w);
    }
    if (at == 96) { const uint2 e = timer_edge(); sts_u2(aCal, e.x, e.y); }
    int lim = POLL_LIM;
    const uint32_t l8c = opaque(lane * 8);
    const uint32_t pA = peer_base(sb, r0), pB = peer_base(sb, r0 + 2 - (j >> 1));
    const uint32_t uR = xchunk(red * 4 + (w & 2), myp) + (w & 1) * 2048;
    const uint32_t uW = xchunk(XC_G2N + (red >> 4) * 4, (myp ^ w ^ 1) & 1) + (red & 15) * 256;
    const uint32_t uG = xchunk(XC_G2N, myp) + w * 512;
    const uint64_t dWo = make_desc(SB + R_WO, 1024, 1024, 1), dO = make_desc(SB + R_O, 128, 128, 0);
#pragma unroll 1
    for (int s = 0; s < NSEG; s++) {
      const uint32_t tag = (s & 1) ^ 1, par = s & 1;
      const bool more = s + 1 < NSEG;
      uint32_t l8 = l8c;
      asm volatile("" : "+r"(l8));
#define STORE_OX(n, w) do {                                                                 \
          tma_store_2d(&maps.ox, sb + R_O + (w) * 1024, h * 128 + (w) * 16, (n) * 32);         \
          tma_store_2d(&maps.ox, sb + R_TS + (w) * 1280, h * 128 + 64 + (w) * 16, (n) * 32); } while (0)
      bar_sync(BAR_MEM, 384);
      if (w == 3) {
        if (l8 == 0) {
          const uint32_t ta = ld_rlx1(XP(XC_T << 12));
          if (more) {
            fence_async_smem();
            xn_pair(&maps.xn2, sb + R_XN, bX, 16384, s + 1, 0, 0);
            mbar_expect_tx(bS, isA ? 2048 : 1280);
          }
          if (!isA) mbar_expect_tx(bTs, 5120);
          const uint4 o = lds_u4(aCal);
          const uint2 e = timer_edge();
          float f = (float)(e.y - o.y) * rcp((float)(e.x - o.x));
          if (s > 1) f = 0.75f * asf(o.z) + 0.25f * f;
          uint32_t d = (int)((float)(int)(ta - e.x) * f);
          if (d > 8192) d = 0;
          sts_u4(aCal, make_uint4(e.x, e.y, asu(f), ta));
#pragma unroll
          for (int i = 0; i < 4; i++) sts_u1(sb + R_TAB + i * 32 + 24, e.y + d);
        }
        if (s + PFX < NSEG && l8 < 128)
          asm volatile("prefetch.global.L2 [%0];" ::"l"(g_xn + (size_t)(s + PFX) * 32 * D_ + (cta & 31) * 1024 + l8 * 8));
      }
#define XN23() do { if (w == 3 && l8 == 0 && more) { fence_async_smem(); xn_pair(&maps.xn2, sb + R_MEM, bX + 8, 16384, s + 1, 2, 0); } __syncwarp(); } while (0)
      if (s == 0 && at == 0) TG(2, 3);
      if (s == 0) mbar_wait(bWo, 0);
      if (s == 0 && at == 0) TG(2, 2);
      if (isA && more && w < 3) {
        uint32_t k[4][4], q[4][4];
        uint32_t ak = sb + R_K + w * 2048 + l8 * 2 + (l8 & 128) * 6, aq = sb + R_Q + 4096 + (l8 & 63) * 2 + (l8 & 64) * 16 + (l8 & 128);
        asm volatile("" : "+r"(ak), "+r"(aq));
        if (w == 2) bar_sync(BAR_RED, 384);
#pragma unroll
        for (int i = 0; i < 4; i++) ldsm4(k[i], ak + i * 256);
        if (w != 2) bar_sync(BAR_RED, 384);
#pragma unroll
        for (int i = 0; i < 4; i++) ldsm4(q[i], aq + i * 256);
        float c[4][4];
#pragma unroll
        for (int i = 0; i < 4; i++) c[i][0] = c[i][1] = c[i][2] = c[i][3] = 0.f;
#pragma unroll
        for (int i = 0; i < 4; i++) {
          mma16816(c[i & 1], q[i][0], q[i][1], q[i][2], q[i][3], k[i][0], k[i][1]);
          mma16816(c[2 + (i & 1)], q[i][0], q[i][1], q[i][2], q[i][3], k[i][2], k[i][3]);
        }
        const float a0 = (c[0][0] + c[0][2]) + (c[1][0] + c[1][2]), a1 = (c[0][1] + c[0][3]) + (c[1][1] + c[1][3]);
        const float b0 = (c[2][0] + c[2][2]) + (c[3][0] + c[3][2]), b1 = (c[2][1] + c[2][3]) + (c[3][1] + c[3][3]);
        const uint32_t as = sb + R_SC + j * 640 + w * 256;
        if (w < 2) {
          const uint32_t x = pack_bf16(a0, a1), y = pack_bf16(b0, b1);
          sta2(as + l8 + pB, x, y, bS + pB);
        } else {
          const uint32_t x = pack_bf16(a0 + b0, a1 + b1);
          sta1(as + (l8 >> 1) + pB, x, bS + pB);
        }
        bar_arrive(BAR_X, 352);
        if (w == 0) TR(2);
      } else if (isA) {
        bar_sync(BAR_RED, 384);
        if (w < 3) bar_arrive(BAR_X, 352);
        XN23();
      } else {
        if (w < 2 && l8 == 0) {
          if (s > 0) {
            fence_async_smem();
            STORE_OX(s - 1, 2 * w); STORE_OX(s - 1, 2 * w + 1);
            asm volatile("cp.async.bulk.commit_group; cp.async.bulk.wait_group.read 0;" ::: "memory");
          }
          arrive_remote(bIn + pA); arrive_remote(bIn + pB);
          if (!more) { asm volatile("cp.async.bulk.wait_group 0;" ::: "memory"); sig_cnt(C_OX + s - 1, 2); }
        }
        __syncwarp();
        uint4 vx[4];
#pragma unroll
        for (int i = 0; i < 4; i++) vx[i] = lds_u4(sb + R_VX + (i & 1) * 1024 + (i >> 1) * 512 + w * 2048 + l8 * 2);
        bar_sync(BAR_RED, 384);
        XN23();
        if (more) {
          const uint32_t am = sb + R_VM + w * 512 + l8 * 2;
          const uint2 vm[4] = {lds_u2(am), lds_u2(am + 2056), lds_u2(am + 8), lds_u2(am + 2048)};
          mbar_wait(bS, par);
          if (w == 0) TR(4);
          float sc[10];
          const uint2 u0 = lds_u2(sb + R_SC + l8), u1 = lds_u2(sb + R_SC + 256 + l8), v0 = lds_u2(sb + R_SC + 640 + l8), v1 = lds_u2(sb + R_SC + 896 + l8);
          sum_scores(sc, u0, u1, lds_u1(sb + R_SC + 512 + (l8 >> 1)), v0, v1, lds_u1(sb + R_SC + 1152 + (l8 >> 1)));
          uint32_t p[5];
          softmax_e(sc);
#pragma unroll
          for (int i = 0; i < 5; i++) p[i] = pack_bf16(sc[2 * i], sc[2 * i + 1]);
          if (w == 0) TR(5);
          float o0[4], o1[4], sm[4];
          pv_mma(o0, o1, sm, vx, vm, p);
          const float i0 = rcp(sm[0]), i1 = rcp(sm[1]);
          const uint32_t aO = sb + R_O + w * 512 + (l8 >> 1);
          const uint32_t o[4] = {pack_bf16(o0[0] * i0, o0[1] * i1), pack_bf16(o0[2] * i0, o0[3] * i1), pack_bf16(o1[0] * i0, o1[1] * i1), pack_bf16(o1[2] * i0, o1[3] * i1)};
#pragma unroll
          for (int i = 0; i < 4; i++) { sta1(aO + i * 128 + pA, o[i], bS + pA); sta1(aO + i * 128 + pB, o[i], bS + pB); }
#pragma unroll
          for (int i = 0; i < 4; i++) sts_u1(aO + i * 128, o[i]);
          asm volatile("cp.async.bulk.wait_group 0;" ::: "memory");
        }
      }
      if (!more && isA) break;
      const uint32_t ts = sb + R_TS + w * 1280;
      uint4 tu, tv;
      uint32_t tu4, tv4, tp = 0;
#define LOAD_TS() tu = lds_u4(ts + l8 * 2); tv = lds_u4(ts + 640 + l8 * 2); tu4 = lds_u1(ts + 512 + (l8 >> 1)); tv4 = lds_u1(ts + 1152 + (l8 >> 1))
      if (!more) {
        mbar_wait(bTs, par);
        LOAD_TS();
      } else {
        float m[6][4];
        const uint4 ta = lds_u4(sb + R_TAB + w * 32);
        const uint4 tb = lds_u4(sb + R_TAB + w * 32 + 16);
        tp = tb.z;
        if (isA) mbar_wait(bS, par);
        else bar_sync(BAR_ST, 160);
        fence_async_smem();
        if (w == 0) TR(8);
        WG_FENCE();
#define WO_GROUP(t0, t1)                                                                                          \
  _Pragma("unroll") for (int kk = 0; kk < 8; kk++) _Pragma("unroll") for (int i = t0; i < t1; i++)                \
      wgmma_n8_tt(m[i], dWo + i * 1024 + kk * 128, dO + (kk & 3) * 32 + (kk >> 2) * 16, kk != 0);                 \
  WG_COMMIT();
        WO_GROUP(0, 3)
        if (isA) { wgmma_n8_tt(m[5], dWo, dO, 0); WO_GROUP(3, 5) } else { WO_GROUP(3, 6) }
#define G1_SEND(i, lo) st_rlx2(xptr(lo + l8, xhi), tagu(pack_bf16(m[i][0], m[i][1]), tag), pack_bf16(m[i][2], m[i][3]))
#define PIN4(i) asm volatile("" : "+f"(m[i][0]), "+f"(m[i][1]), "+f"(m[i][2]), "+f"(m[i][3]))
        WG_WAIT(1);
        PIN4(0); PIN4(1); PIN4(2);
        G1_SEND(0, ta.x); G1_SEND(1, ta.y); G1_SEND(2, ta.z);
        mbar_wait(isA ? bS : bTs, par);
        LOAD_TS();
        WG_WAIT(0);
        PIN4(3); PIN4(4); PIN4(5);
        bar_arrive(BAR_BG, 384);
        G1_SEND(3, ta.w); G1_SEND(4, tb.x);
        if (!isA) G1_SEND(5, tb.y);
        if (w == 0) TR(9);
      }
      const uint32_t slot = ((s & 1) * 48 + (s & 2) * 32) << 12;
      asm volatile("" : "+r"(l8));
      if (isA) {
        const unsigned char* pR = XP(uR + l8);
        unsigned char* pW = XP(((uW + slot) ^ ((w & 2) << 17)) + l8);
        uint32_t sel = (l8 >> 6) == ((l8 >> 3) & 3) ? (l8 & 32 ? 0x3F800000u : 0x3F80u) : 0;
        asm volatile("" : "+r"(sel), "+l"(pR), "+l"(pW));
        uint32_t ci = wait_clk(tp, D_G1), bad;
        if (w == 0) TRX(10, ci);
#pragma unroll 1
        do {
          uint2 p[8];
#pragma unroll
          for (int i = 0; i < 8; i++) p[i] = ld_rlx2(pR + i * 256);
          ci = clk32();
          float d[2][4] = {};
#pragma unroll
          for (int i = 0; i < 4; i++) mma16816(d[i & 1], p[2 * i].x, p[2 * i].y, p[2 * i + 1].x, p[2 * i + 1].y, sel, sel);
          bad = or3(ne2(p[0].x, p[1].x, tag), ne2(p[2].x, p[3].x, tag), ne2(p[4].x, p[5].x, tag)) | ne2(p[6].x, p[7].x, tag);
          sts_u2(sb + R_G1 + w * 512 + l8, asu(d[0][0] + d[1][0]), asu(d[0][1] + d[1][1]));
          sts_u2(sb + R_G1 + w * 512 + 256 + l8, asu(d[0][2] + d[1][2]), asu(d[0][3] + d[1][3]));
        } while (__any_sync(~0u, (bad & 1) && --lim > 0));
        bar_sync(BAR_G1, 128);
        if (w < 2) {
          const float4 a = lds_f4(sb + R_G1 + l8 * 2), b = lds_f4(sb + R_G1 + 512 + l8 * 2), c = lds_f4(sb + R_G1 + 1024 + l8 * 2), d = lds_f4(sb + R_G1 + 1536 + l8 * 2);
          st_rlx2(pW, nz(pack_bf16((a.x + b.x) + (c.x + d.x), (a.y + b.y) + (c.y + d.y))),
                  nz(pack_bf16((a.z + b.z) + (c.z + d.z), (a.w + b.w) + (c.w + d.w))));
        } else {
          st_rlx2(pW, 0, 0);
        }
        bar_arrive(BAR_H, 384);
        if (w == 0) TR(12);
        if (w == 0) TRX(11, ci);
        if (cta == 0 && w == 3) {
          const uint4 o = lds_u4(aCal);
          const bool late = (int)(ci - tp) > 200;
          st_rlx1(XP(XC_T << 12), (late ? o.x : o.w) + (int)((float)(int)(T_STEP + (late ? ci - o.y + T_REL : 0)) * rcp(asf(o.z))));
        }
      } else {
        const uint32_t av = sb + R_VX + w * 2048 + l8 * 2, am = sb + R_VM + w * 512 + l8 * 2;
        float sc[10];
        sum_scores(sc, make_uint2(tu.x, tu.y), make_uint2(tu.z, tu.w), tu4, make_uint2(tv.x, tv.y), make_uint2(tv.z, tv.w), tv4);
        uint4 x = lds_u4(av), y = lds_u4(av + 512);
        uint2 m0 = lds_u2(am), m1 = lds_u2(am + 2056);
        const int lim_k = w * 8 + (l8 >> 5) - ((l8 >> 2) & 6);
#pragma unroll
        for (int i = 0; i < 8; i++)
          if ((i >> 1) * 8 + (i & 1) > lim_k) sc[i] = -1.0e9f * 11.313708498984761f;
        softmax_e(sc);
        float sum = ((sc[0] + sc[1]) + (sc[2] + sc[3])) + ((sc[4] + sc[5]) + (sc[6] + sc[7])) + (sc[8] + sc[9]);
        sum += __shfl_xor_sync(~0u, sum, 1);
        sum += __shfl_xor_sync(~0u, sum, 2);
        const float inv = rcp(sum);
#pragma unroll
        for (int i = 0; i < 6; i++) sts_u1(ts + i * 128 + (l8 >> 1), pack_bf16(sc[i < 5 ? 2 * i : 8] * inv, sc[i < 5 ? 2 * i + 1 : 9] * inv));
        fence_async_smem();
        bar_sync(BAR_O, 128);
        const uint32_t ao = sb + (l8 & 128) * 2 + (l8 & 56) * 4 + (((l8 >> 2) ^ (l8 >> 1)) & 16);
#pragma unroll
        for (int t = 0; t < 2; t++) {
          const uint32_t a0[4] = {x.x, x.y, x.z, x.w}, a1[4] = {y.x, y.y, y.z, y.w}, a2[4] = {m0.x, m0.y, m1.x, m1.y};
          float d[16];
          WG_FENCE();
          wgmma_rs32(d, a0, make_desc(SB + R_TS, 128, 1280, 0), 0);
          wgmma_rs32(d, a1, make_desc(SB + R_TS + 256, 128, 1280, 0), 1);
          wgmma_rs32(d, a2, make_desc(SB + R_TS + 512, 128, 1280, 0), 1);
          WG_COMMIT();
          if (t == 0) { x = lds_u4(av + 1024); y = lds_u4(av + 1536); m0 = lds_u2(am + 8); m1 = lds_u2(am + 2048); }
          WG_WAIT(0);
          asm volatile("" : D16(d));
          if (t == 0) {
#define CPY(v) asm volatile("or.b32 %0, %0, %1;" : "+r"(v) : "r"(c_tune[15]))
            CPY(x.x); CPY(x.y); CPY(x.z); CPY(x.w); CPY(y.x); CPY(y.y); CPY(y.z); CPY(y.w); CPY(m0.x); CPY(m0.y); CPY(m1.x); CPY(m1.y);
            __syncwarp();
            if (l8 == 0) mbar_arrive(bTok);
          }
          stsm4t(ao + (t ? R_TS + w * 1280 : R_O + w * 1024), pack_bf16(d[0], d[1]), pack_bf16(d[2], d[3]), pack_bf16(d[4], d[5]), pack_bf16(d[6], d[7]));
          stsm4t(ao + (t ? R_TS + w * 1280 : R_O + w * 1024) + 512, pack_bf16(d[8], d[9]), pack_bf16(d[10], d[11]), pack_bf16(d[12], d[13]), pack_bf16(d[14], d[15]));
        }
        if (w == 0) TR(13);
        if (!more) {
          fence_async_smem();
          __syncwarp();
          if (l8 == 0) {
            STORE_OX(s, w);
            asm volatile("cp.async.bulk.commit_group; cp.async.bulk.wait_group 0;" ::: "memory");
            sig_cnt(C_OX + s);
            if (w == 0) TG(0, 3);
            if (cta == 2) ST(4);
          }
          break;
        }
      }
      {
        const unsigned char* src = XP(uG + slot + l8 * 2);
        const uint32_t dst = sb + R_MEM + w * 512 + l8 * 2;
        wait_clk(tp + T_G2, isA ? D_G2 : 0);
        if (w == 0) TR(16);
        uint4 p[8];
#pragma unroll
        for (int i = 0; i < 8; i++) p[i] = ld_rlx4(src + (i >> 1) * 16384 + (i & 1) * 2048);
        mbar_wait(bM, par ^ 1);
        uint32_t mn = ~0u, ck = 0;
#pragma unroll
        for (int i = 0; i < 8; i += 2) {
          mn = __vimin3_u32(mn, p[i].x, p[i + 1].x);
          asm volatile("" : "+r"(mn));
          sts_u4(dst + i * 2048, p[i]);
          sts_u4(dst + i * 2048 + 2048, p[i + 1]);
          mn = __vimin3_u32(mn, __vimin3_u32(p[i].y, p[i].z, p[i].w), __vimin3_u32(p[i + 1].y, p[i + 1].z, p[i + 1].w));
          asm volatile("" : "+r"(mn));
        }
        if (__builtin_expect(__any_sync(~0u, mn == 0u), 0)) {
#pragma unroll 1
          do {
#pragma unroll
            for (int i = 0; i < 8; i++) reld4(p[i], src + (i >> 1) * 16384 + (i & 1) * 2048, min4(p[i]));
            mn = ~0u;
#pragma unroll
            for (int i = 0; i < 8; i++) { sts_u4(dst + i * 2048, p[i]); mn = min(mn, min4(p[i])); }
          } while (__any_sync(~0u, mn == 0u && --lim > 0));
          lim = after(lim, ck, 0);
        }
        if (w == 0) TR(15);
      }
    }
  }
  asm volatile("barrier.cluster.arrive.relaxed.aligned; barrier.cluster.wait.aligned;" ::: "memory");
}

typedef CUresult (*EncodeFn)(CUtensorMap*, CUtensorMapDataType, cuuint32_t, void*, const cuuint64_t*, const cuuint64_t*,
                             const cuuint32_t*, const cuuint32_t*, CUtensorMapInterleave, CUtensorMapSwizzle,
                             CUtensorMapL2promotion, CUtensorMapFloatOOBfill);
static EncodeFn g_encode = nullptr;

#define PROMO CU_TENSOR_MAP_L2_PROMOTION_L2_256B
static void map2d(CUtensorMap* m, const void* p, uint64_t cols, uint64_t rows, uint32_t bc, uint32_t br,
                  CUtensorMapSwizzle sw) {
  cuuint64_t dims[2] = {cols, rows}, strides[1] = {cols * 2};
  cuuint32_t box[2] = {bc, br}, es[2] = {1, 1};
  g_encode(m, CU_TENSOR_MAP_DATA_TYPE_BFLOAT16, 2, (void*)p, dims, strides, box, es, CU_TENSOR_MAP_INTERLEAVE_NONE, sw,
           sw == CU_TENSOR_MAP_SWIZZLE_64B ? PROMO : CU_TENSOR_MAP_L2_PROMOTION_L2_256B, CU_TENSOR_MAP_FLOAT_OOB_FILL_NONE);
}
static void map_w(CUtensorMap* m, const void* p, uint64_t N, uint64_t K) {
  cuuint64_t dims[3] = {64, K, N / 64}, strides[2] = {N * 2, 128};
  cuuint32_t box[3] = {64, 64, 2}, es[3] = {1, 1, 1};
  g_encode(m, CU_TENSOR_MAP_DATA_TYPE_BFLOAT16, 3, (void*)p, dims, strides, box, es, CU_TENSOR_MAP_INTERLEAVE_NONE,
           CU_TENSOR_MAP_SWIZZLE_128B, CU_TENSOR_MAP_L2_PROMOTION_L2_256B, CU_TENSOR_MAP_FLOAT_OOB_FILL_NONE);
}
static void map_seg(CUtensorMap* m, const void* p, uint64_t K, uint64_t parts, uint32_t np, CUtensorMapL2promotion pr = CU_TENSOR_MAP_L2_PROMOTION_L2_256B) {
  cuuint64_t dims[4] = {64, S_, K / 64 / parts, parts}, strides[3] = {K * 2, 128, K * 2 / parts};
  cuuint32_t box[4] = {64, 32, 2, np}, es[4] = {1, 1, 1, 1};
  g_encode(m, CU_TENSOR_MAP_DATA_TYPE_BFLOAT16, 4, (void*)p, dims, strides, box, es, CU_TENSOR_MAP_INTERLEAVE_NONE,
           CU_TENSOR_MAP_SWIZZLE_128B, pr, CU_TENSOR_MAP_FLOAT_OOB_FILL_NONE);
}
template <typename T>
static void* sym(T& s) { void* p = nullptr; cudaGetSymbolAddress(&p, s); return p; }

static void map_a(CUtensorMap* m, const void* p, int K) { map2d(m, p, K, S_, 64, 128, CU_TENSOR_MAP_SWIZZLE_128B); }
static void map_c(CUtensorMap* m, const void* p, int N) { map2d(m, p, N, S_, 64, 16, CU_TENSOR_MAP_SWIZZLE_128B); }

extern "C" void kernel_launch(void* const* d_in, const int* in_sizes, int n_in, void* d_out, int out_size) {
  const bf16* x = (const bf16*)d_in[0];
  const bf16* mem0 = (const bf16*)d_in[1];
  const bf16* Wo = (const bf16*)d_in[5];
  const bf16* w1 = (const bf16*)d_in[8];
  const bf16* w2 = (const bf16*)d_in[9];
  const bf16* w3 = (const bf16*)d_in[10];
  const bf16* w4 = (const bf16*)d_in[11];
  if (!g_encode) {
    void* fn = nullptr;
    cudaDriverEntryPointQueryResult qr;
    cudaGetDriverEntryPoint("cuTensorMapEncodeTiled", &fn, cudaEnableDefault, &qr);
    g_encode = (EncodeFn)fn;
    cudaFuncSetAttribute(k_gemm, cudaFuncAttributeMaxDynamicSharedMemorySize, G_SMEM);
    cudaFuncSetAttribute(k_rec, cudaFuncAttributeMaxDynamicSharedMemorySize, R_SMEM);
  }
  const bf16 *xn = (bf16*)sym(g_xn), *xn2 = (bf16*)sym(g_xn2), *gate = (bf16*)sym(g_gate), *ox = (bf16*)sym(g_ox),
             *h1 = (bf16*)sym(g_h1), *x1 = (bf16*)sym(g_x1), *ln1 = (bf16*)sym(g_ln1), *h3 = (bf16*)sym(g_h3);
  GemmMaps gm;
  map_a(&gm.a[0], xn2, D_); map_a(&gm.a[1], h1, D_); map_a(&gm.a[2], ln1, D_); map_a(&gm.a[3], h3, F_); map_a(&gm.a[4], ox, 4096);
  map_w(&gm.b[0], w1, D_, D_); map_w(&gm.b[1], w2, D_, D_); map_w(&gm.b[2], w3, F_, D_); map_w(&gm.b[3], w4, D_, F_);
  map_w(&gm.b[4], Wo, D_, 4096);
  map_c(&gm.c[0], h1, D_); map_c(&gm.c[1], x1, D_); map_c(&gm.c[2], h3, F_); map_c(&gm.c[3], gate, D_); map_c(&gm.c[4], d_out, D_);
  map_c(&gm.c[5], ln1, D_);
  map_a(&gm.e[0], xn, D_); map_a(&gm.e[1], x1, D_); map_a(&gm.e[2], gate, D_); map_a(&gm.e[3], x, D_);
  map_w(&gm.od, ox, 4096, S_);
  RecMaps rm;
  for (int i = 0; i < 3; i++) {
    map2d(&rm.w[i], d_in[2 + i], 4096, D_, 64, 16, CU_TENSOR_MAP_SWIZZLE_128B);
    map2d(&rm.wb[i], d_in[2 + i], 4096, D_, 64, 256, CU_TENSOR_MAP_SWIZZLE_128B);
  }
  map2d(&rm.wo, Wo, D_, 4096, 64, 128, CU_TENSOR_MAP_SWIZZLE_128B);
  map2d(&rm.xn, xn, D_, S_, 64, 32, CU_TENSOR_MAP_SWIZZLE_128B);
  map_seg(&rm.xn1, xn, D_, 2, 1); map_seg(&rm.xn2, xn, D_, 2, 2);
  map2d(&rm.ox, ox, 4096, S_, 16, 32, CU_TENSOR_MAP_SWIZZLE_32B);
  unsigned char* xch = (unsigned char*)(((uintptr_t)sym(g_xch) + 2 * XPAGE - 1) & ~(uintptr_t)(2 * XPAGE - 1));
  cudaLaunchAttribute at[1];
  at[0].id = cudaLaunchAttributeClusterDimension;
  at[0].val.clusterDim.x = 6; at[0].val.clusterDim.y = 1; at[0].val.clusterDim.z = 1;
  cudaLaunchConfig_t cfg = {};
  cfg.attrs = at; cfg.numAttrs = 1; cfg.stream = cudaStreamPerThread;
  cfg.gridDim = dim3(96); cfg.blockDim = dim3(384); cfg.dynamicSmemBytes = R_SMEM;
  cudaLaunchKernelEx(&cfg, k_rec, rm, x, mem0, xch);
  at[0].id = cudaLaunchAttributeProgrammaticStreamSerialization;
  at[0].val.programmaticStreamSerializationAllowed = 1;
  cfg.gridDim = dim3(2 * NPAIR); cfg.dynamicSmemBytes = G_SMEM;
  cudaLaunchKernelEx(&cfg, k_gemm, gm, x, (bf16*)d_out);
}
```

```cpp
#include <cuda_runtime.h>
#include <cuda_bf16.h>
#include <cuda.h>
#include <stdint.h>

typedef __nv_bfloat16 bf16;

constexpr int S_ = 2048, D_ = 1024, H_ = 32, DH_ = 128, F_ = 3584, NSEG = 64;

__device__ __align__(1024) bf16 g_xn[S_ * D_];
__device__ __align__(1024) bf16 g_xn2[S_ * D_];
__device__ __align__(1024) bf16 g_ox[S_ * H_ * DH_];
__device__ __align__(1024) bf16 g_h1[S_ * D_];
__device__ __align__(1024) bf16 g_x1[S_ * D_];
__device__ __align__(1024) bf16 g_ln1[S_ * D_];
__device__ __align__(1024) bf16 g_h3[S_ * F_];
__device__ __align__(1024) bf16 g_gate[S_ * D_];
__device__ __align__(1024) uint4 g_dx[32 * 16 * 512];
__device__ __align__(1024) uint2 g_rstat[S_ * 4];

constexpr int XPAGE = 1 << 21;
__device__ __align__(4096) unsigned char g_xch[4 * XPAGE];
__device__ __forceinline__ uint32_t xchunk(int c, int p) { return (uint32_t)(c | ((__popc(c & 0xb3) & 1) ^ p)) << 12; }

#define TR(i)
#define TRB(i)
#define TRX(i, v)
#define TRV(i, v)
#define TG(r, i)
#define TRCAL(k)
#define ST(i)
__device__ __forceinline__ uint32_t smem_u32(const void* p) { return (uint32_t)__cvta_generic_to_shared(p); }
__device__ __forceinline__ void mbar_init(uint32_t bar, int cnt) {
  asm volatile("mbarrier.init.shared::cta.b64 [%0], %1;" ::"r"(bar), "r"(cnt) : "memory");
}
__device__ __forceinline__ void mbar_expect_tx(uint32_t bar, int bytes) {
  asm volatile("mbarrier.arrive.expect_tx.shared::cta.b64 _, [%0], %1;" ::"r"(bar), "r"(bytes) : "memory");
}
__device__ __forceinline__ void mbar_arrive(uint32_t bar) {
  asm volatile("mbarrier.arrive.shared::cta.b64 _, [%0];" ::"r"(bar) : "memory");
}
__device__ __forceinline__ void mbar_wait(uint32_t bar, uint32_t parity) {
  uint32_t ok;
  int n = 0;
  do {
    asm volatile(
        "{.reg .pred p; mbarrier.try_wait.parity.shared::cta.b64 p, [%1], %2; selp.u32 %0, 1, 0, p;}"
        : "=r"(ok) : "r"(bar), "r"(parity) : "memory");
  } while (!ok && ++n < (1 << 22));
}
__device__ __forceinline__ void mbar_wait_long(uint32_t bar, uint32_t parity) {
  uint32_t ok;
  int n = 0;
#pragma unroll 1
  do {
    asm volatile(
        "{.reg .pred p; mbarrier.try_wait.parity.shared::cta.b64 p, [%1], %2, 2000; selp.u32 %0, 1, 0, p;}"
        : "=r"(ok) : "r"(bar), "r"(parity) : "memory");
  } while (!ok && ++n < (1 << 22));
}
__device__ __forceinline__ void tma_load_2d(uint32_t dst, const CUtensorMap* m, int c0, int c1, uint32_t bar) {
  asm volatile(
      "cp.async.bulk.tensor.2d.shared::cluster.global.mbarrier::complete_tx::bytes [%0], [%1, {%3, %4}], [%2];"
      ::"r"(dst), "l"(m), "r"(bar), "r"(c0), "r"(c1) : "memory");
}
__device__ __forceinline__ void tma_load_2d_ef(uint32_t dst, const CUtensorMap* m, int c0, int c1, uint32_t bar) {
  asm volatile(
      "{.reg .b64 pol; createpolicy.fractional.L2::evict_first.b64 pol, 1.0;\n"
      "cp.async.bulk.tensor.2d.shared::cluster.global.mbarrier::complete_tx::bytes.L2::cache_hint [%0], [%1, {%3, %4}], [%2], pol;}"
      ::"r"(dst), "l"(m), "r"(bar), "r"(c0), "r"(c1) : "memory");
}
__device__ __forceinline__ void tma_load_3d(uint32_t dst, const CUtensorMap* m, int c0, int c1, int c2, uint32_t bar) {
  asm volatile(
      "cp.async.bulk.tensor.3d.shared::cluster.global.mbarrier::complete_tx::bytes [%0], [%1, {%3, %4, %5}], [%2];"
      ::"r"(dst), "l"(m), "r"(bar), "r"(c0), "r"(c1), "r"(c2) : "memory");
}
__device__ __forceinline__ void tma_store_2d(const CUtensorMap* m, uint32_t src, int c0, int c1) {
  asm volatile("cp.async.bulk.tensor.2d.global.shared::cta.bulk_group [%0, {%2, %3}], [%1];"
               ::"l"(m), "r"(src), "r"(c0), "r"(c1) : "memory");
}
__device__ __forceinline__ uint64_t policy(bool stream) {
  uint64_t a, b;
  asm("createpolicy.fractional.L2::evict_first.b64 %0, 1.0;" : "=l"(a));
  asm("createpolicy.fractional.L2::evict_normal.b64 %0, 1.0;" : "=l"(b));
  return stream ? a : b;
}
__device__ __forceinline__ void tma_store_2d_p(const CUtensorMap* m, uint32_t src, int c0, int c1, uint64_t pol) {
  asm volatile("cp.async.bulk.tensor.2d.global.shared::cta.bulk_group.L2::cache_hint [%0, {%2, %3}], [%1], %4;"
               ::"l"(m), "r"(src), "r"(c0), "r"(c1), "l"(pol) : "memory");
}
__device__ __forceinline__ void tma_prefetch_2d(const CUtensorMap* m, int c0, int c1) {
  asm volatile("cp.async.bulk.prefetch.tensor.2d.L2.global [%0, {%1, %2}];" ::"l"(m), "r"(c0), "r"(c1) : "memory");
}
__device__ __forceinline__ void tma_prefetch_3d(const CUtensorMap* m, int c0, int c1, int c2) {
  asm volatile("cp.async.bulk.prefetch.tensor.3d.L2.global [%0, {%1, %2, %3}];" ::"l"(m), "r"(c0), "r"(c1), "r"(c2) : "memory");
}
__device__ __forceinline__ uint32_t clk32() { uint32_t c; asm volatile("mov.u32 %0, %%clock;" : "=r"(c)::"memory"); return c; }
__device__ __forceinline__ uint32_t ld_rlx1(const void* p) { uint32_t v; asm volatile("ld.relaxed.gpu.global.u32 %0, [%1];" : "=r"(v) : "l"(p) : "memory"); return v; }
__device__ __forceinline__ uint32_t smid() { uint32_t c; asm volatile("mov.u32 %0, %%smid;" : "=r"(c)); return c; }
__device__ __forceinline__ void fence_async_smem() { asm volatile("fence.proxy.async.shared::cta;" ::: "memory"); }
__device__ __forceinline__ void bar_sync(int id, int n) { asm volatile("bar.sync %0, %1;" ::"r"(id), "r"(n) : "memory"); }
__device__ __forceinline__ void bar_arrive(int id, int n) { asm volatile("bar.arrive %0, %1;" ::"r"(id), "r"(n) : "memory"); }
__host__ __device__ constexpr uint64_t make_desc(uint32_t addr, uint32_t lbo, uint32_t sbo, uint32_t mode) {
  return (uint64_t)((addr & 0x3FFFF) >> 4) | ((uint64_t)(lbo >> 4) << 16) | ((uint64_t)(sbo >> 4) << 32) |
         ((uint64_t)mode << 62);
}
#define WG_FENCE() asm volatile("wgmma.fence.sync.aligned;" ::: "memory")
#define WG_COMMIT() asm volatile("wgmma.commit_group.sync.aligned;" ::: "memory")
#define WG_WAIT(n) asm volatile("wgmma.wait_group.sync.aligned " #n ";" ::: "memory")

__device__ __forceinline__ uint32_t pack_bf16(float lo, float hi) {
  uint32_t r;
  asm("cvt.rn.bf16x2.f32 %0, %1, %2;" : "=r"(r) : "f"(hi), "f"(lo));
  return r;
}
__device__ __forceinline__ float bf_lo(uint32_t v) { return __uint_as_float(v << 16); }
__device__ __forceinline__ float bf_hi(uint32_t v) { return __uint_as_float(v & 0xffff0000u); }
__device__ __forceinline__ float rbf(float x) { return __bfloat162float(__float2bfloat16_rn(x)); }

__device__ __forceinline__ void ldsm4(uint32_t* r, uint32_t a) {
  asm volatile("ldmatrix.sync.aligned.m8n8.x4.shared.b16 {%0,%1,%2,%3}, [%4];"
               : "=r"(r[0]), "=r"(r[1]), "=r"(r[2]), "=r"(r[3]) : "r"(a) : "memory");
}
__device__ __forceinline__ void ldsm4t(uint32_t* r, uint32_t a) {
  asm volatile("ldmatrix.sync.aligned.m8n8.x4.trans.shared.b16 {%0,%1,%2,%3}, [%4];"
               : "=r"(r[0]), "=r"(r[1]), "=r"(r[2]), "=r"(r[3]) : "r"(a) : "memory");
}
__device__ __forceinline__ void stsm4(uint32_t a, uint32_t r0, uint32_t r1, uint32_t r2, uint32_t r3) {
  asm volatile("stmatrix.sync.aligned.m8n8.x4.shared.b16 [%0], {%1,%2,%3,%4};"
               ::"r"(a), "r"(r0), "r"(r1), "r"(r2), "r"(r3) : "memory");
}
__device__ __forceinline__ void stsm4t(uint32_t a, uint32_t r0, uint32_t r1, uint32_t r2, uint32_t r3) {
  asm volatile("stmatrix.sync.aligned.m8n8.x4.trans.shared.b16 [%0], {%1,%2,%3,%4};"
               ::"r"(a), "r"(r0), "r"(r1), "r"(r2), "r"(r3) : "memory");
}
__device__ __forceinline__ void mma16816(float* d, uint32_t a0, uint32_t a1, uint32_t a2, uint32_t a3, uint32_t b0,
                                         uint32_t b1) {
  asm(
      "mma.sync.aligned.m16n8k16.row.col.f32.bf16.bf16.f32 {%0,%1,%2,%3}, {%4,%5,%6,%7}, {%8,%9}, {%0,%1,%2,%3};"
      : "+f"(d[0]), "+f"(d[1]), "+f"(d[2]), "+f"(d[3]) : "r"(a0), "r"(a1), "r"(a2), "r"(a3), "r"(b0), "r"(b1));
}
__device__ __forceinline__ void mma16816c(float* d, const float* c, uint32_t a0, uint32_t a1, uint32_t a2, uint32_t a3,
                                          uint32_t b0, uint32_t b1) {
  asm volatile(
      "mma.sync.aligned.m16n8k16.row.col.f32.bf16.bf16.f32 {%0,%1,%2,%3}, {%4,%5,%6,%7}, {%8,%9}, {%10,%11,%12,%13};"
      : "=f"(d[0]), "=f"(d[1]), "=f"(d[2]), "=f"(d[3])
      : "r"(a0), "r"(a1), "r"(a2), "r"(a3), "r"(b0), "r"(b1), "f"(c[0]), "f"(c[1]), "f"(c[2]), "f"(c[3]));
}
__device__ __forceinline__ void mma1688(float* d, uint32_t a0, uint32_t a1, uint32_t b0) {
  asm("mma.sync.aligned.m16n8k8.row.col.f32.bf16.bf16.f32 {%0,%1,%2,%3}, {%4,%5}, {%6}, {%0,%1,%2,%3};"
               : "+f"(d[0]), "+f"(d[1]), "+f"(d[2]), "+f"(d[3]) : "r"(a0), "r"(a1), "r"(b0));
}
__device__ __forceinline__ void wgmma_n8_tt(float* d, uint64_t a, uint64_t b, int scale_d) {
  asm volatile(
      "{.reg .pred p; setp.ne.b32 p, %6, 0;\n"
      "wgmma.mma_async.sync.aligned.m64n8k16.f32.bf16.bf16 {%0,%1,%2,%3}, %4, %5, p, 1, 1, 1, 1;}"
      : "+f"(d[0]), "+f"(d[1]), "+f"(d[2]), "+f"(d[3]) : "l"(a), "l"(b), "r"(scale_d));
}
__device__ __forceinline__ void wgmma_n256(float* d, uint64_t a, uint64_t b, int scale_d) {
  asm volatile(
      "{.reg .pred p; setp.ne.b32 p, %130, 0;\n"
      "wgmma.mma_async.sync.aligned.m64n256k16.f32.bf16.bf16 "
      "{%0,%1,%2,%3,%4,%5,%6,%7,%8,%9,%10,%11,%12,%13,%14,%15,%16,%17,%18,%19,%20,%21,%22,%23,%24,%25,%26,%27,%28,%29,%30,%31,"
      "%32,%33,%34,%35,%36,%37,%38,%39,%40,%41,%42,%43,%44,%45,%46,%47,%48,%49,%50,%51,%52,%53,%54,%55,%56,%57,%58,%59,%60,%61,%62,%63,"
      "%64,%65,%66,%67,%68,%69,%70,%71,%72,%73,%74,%75,%76,%77,%78,%79,%80,%81,%82,%83,%84,%85,%86,%87,%88,%89,%90,%91,%92,%93,%94,%95,"
      "%96,%97,%98,%99,%100,%101,%102,%103,%104,%105,%106,%107,%108,%109,%110,%111,%112,%113,%114,%115,%116,%117,%118,%119,%120,%121,%122,%123,%124,%125,%126,%127},"
      " %128, %129, p, 1, 1, 0, 1;}"
      : "+f"(d[0]), "+f"(d[1]), "+f"(d[2]), "+f"(d[3]), "+f"(d[4]), "+f"(d[5]), "+f"(d[6]), "+f"(d[7]),
        "+f"(d[8]), "+f"(d[9]), "+f"(d[10]), "+f"(d[11]), "+f"(d[12]), "+f"(d[13]), "+f"(d[14]), "+f"(d[15]),
        "+f"(d[16]), "+f"(d[17]), "+f"(d[18]), "+f"(d[19]), "+f"(d[20]), "+f"(d[21]), "+f"(d[22]), "+f"(d[23]),
        "+f"(d[24]), "+f"(d[25]), "+f"(d[26]), "+f"(d[27]), "+f"(d[28]), "+f"(d[29]), "+f"(d[30]), "+f"(d[31]),
        "+f"(d[32]), "+f"(d[33]), "+f"(d[34]), "+f"(d[35]), "+f"(d[36]), "+f"(d[37]), "+f"(d[38]), "+f"(d[39]),
        "+f"(d[40]), "+f"(d[41]), "+f"(d[42]), "+f"(d[43]), "+f"(d[44]), "+f"(d[45]), "+f"(d[46]), "+f"(d[47]),
        "+f"(d[48]), "+f"(d[49]), "+f"(d[50]), "+f"(d[51]), "+f"(d[52]), "+f"(d[53]), "+f"(d[54]), "+f"(d[55]),
        "+f"(d[56]), "+f"(d[57]), "+f"(d[58]), "+f"(d[59]), "+f"(d[60]), "+f"(d[61]), "+f"(d[62]), "+f"(d[63]),
        "+f"(d[64]), "+f"(d[65]), "+f"(d[66]), "+f"(d[67]), "+f"(d[68]), "+f"(d[69]), "+f"(d[70]), "+f"(d[71]),
        "+f"(d[72]), "+f"(d[73]), "+f"(d[74]), "+f"(d[75]), "+f"(d[76]), "+f"(d[77]), "+f"(d[78]), "+f"(d[79]),
        "+f"(d[80]), "+f"(d[81]), "+f"(d[82]), "+f"(d[83]), "+f"(d[84]), "+f"(d[85]), "+f"(d[86]), "+f"(d[87]),
        "+f"(d[88]), "+f"(d[89]), "+f"(d[90]), "+f"(d[91]), "+f"(d[92]), "+f"(d[93]), "+f"(d[94]), "+f"(d[95]),
        "+f"(d[96]), "+f"(d[97]), "+f"(d[98]), "+f"(d[99]), "+f"(d[100]), "+f"(d[101]), "+f"(d[102]), "+f"(d[103]),
        "+f"(d[104]), "+f"(d[105]), "+f"(d[106]), "+f"(d[107]), "+f"(d[108]), "+f"(d[109]), "+f"(d[110]), "+f"(d[111]),
        "+f"(d[112]), "+f"(d[113]), "+f"(d[114]), "+f"(d[115]), "+f"(d[116]), "+f"(d[117]), "+f"(d[118]), "+f"(d[119]),
        "+f"(d[120]), "+f"(d[121]), "+f"(d[122]), "+f"(d[123]), "+f"(d[124]), "+f"(d[125]), "+f"(d[126]), "+f"(d[127])
      : "l"(a), "l"(b), "r"(scale_d));
}

__device__ __forceinline__ uint4 ld_rlx4(const void* p) {
  uint4 v;
  asm volatile("{.reg .b128 r; ld.relaxed.gpu.global.b128 r, [%4]; mov.b128 {%0,%1,%2,%3}, r;}"
               : "=r"(v.x), "=r"(v.y), "=r"(v.z), "=r"(v.w) : "l"(p) : "memory");
  return v;
}
__device__ __forceinline__ uint2 ld_rlx2(const void* p) {
  uint2 v;
  asm volatile("{.reg .b64 r; ld.relaxed.gpu.global.b64 r, [%2]; mov.b64 {%0,%1}, r;}" : "=r"(v.x), "=r"(v.y) : "l"(p) : "memory");
  return v;
}
__device__ __forceinline__ void st_rlx4(void* p, uint32_t a, uint32_t b, uint32_t c, uint32_t d) {
  asm volatile("{.reg .b128 r; mov.b128 r, {%1,%2,%3,%4}; st.relaxed.gpu.global.b128 [%0], r;}"
               ::"l"(p), "r"(a), "r"(b), "r"(c), "r"(d) : "memory");
}
__device__ __forceinline__ void st_rlx2(void* p, uint32_t a, uint32_t b) {
  asm volatile("{.reg .b64 r; mov.b64 r, {%1,%2}; st.relaxed.gpu.global.b64 [%0], r;}" ::"l"(p), "r"(a), "r"(b) : "memory");
}
__device__ __forceinline__ void st_rlx1(void* p, uint32_t a) {
  asm volatile("st.relaxed.gpu.global.u32 [%0], %1;" ::"l"(p), "r"(a) : "memory");
}

__device__ __forceinline__ uint32_t nz(uint32_t v) { return v == 0u ? 0x80000000u : v; }
__device__ __forceinline__ uint32_t tagu(uint32_t v, uint32_t tag) { return (v & ~1u) | tag; }
__device__ __forceinline__ float asf(uint32_t v) { return __uint_as_float(v); }
__device__ __forceinline__ uint32_t asu(float v) { return __float_as_uint(v); }
__device__ __forceinline__ uint32_t opaque(uint32_t x) { return __shfl_sync(~0u, x, threadIdx.x & 31); }
__device__ __forceinline__ unsigned char* xptr(uint32_t lo, uint32_t hi) {
  uint64_t a;
  asm("mov.b64 %0, {%1, %2};" : "=l"(a) : "r"(lo), "r"(hi));
  return (unsigned char*)a;
}
#define DSC(lo) (uint64_t)xptr(lo, (uint32_t)(make_desc(0, 0, 1024, 1) >> 32))
__device__ __forceinline__ void reld4(uint4& v, const void* p, uint32_t m) {
  asm volatile("{.reg .pred q; setp.eq.b32 q, %5, 0; @q ld.relaxed.gpu.global.v4.b32 {%0,%1,%2,%3}, [%4];}"
               : "+r"(v.x), "+r"(v.y), "+r"(v.z), "+r"(v.w) : "l"(p), "r"(m) : "memory");
}
__device__ __forceinline__ uint32_t ne2(uint32_t a, uint32_t b, uint32_t t) {
  uint32_t r;
  asm("lop3.b32 %0, %1, %2, %3, 0x7E;" : "=r"(r) : "r"(a), "r"(b), "r"(t));
  return r;
}
__device__ __forceinline__ uint32_t or3(uint32_t a, uint32_t b, uint32_t c) {
  uint32_t r;
  asm("lop3.b32 %0, %1, %2, %3, 0xFE;" : "=r"(r) : "r"(a), "r"(b), "r"(c));
  return r;
}
__device__ __forceinline__ uint32_t after(uint32_t a, uint32_t dep, uint32_t zero) {
  uint32_t r;
  asm("lop3.b32 %0, %1, %2, %3, 0xF8;" : "=r"(r) : "r"(a), "r"(dep), "r"(zero));
  return r;
}
__device__ __forceinline__ uint32_t wait_clk(uint32_t t, int D) {
  uint32_t c = clk32();
  if ((int)(t - c) < D) t = c + D;
  while ((int)(c - t) < 0) c = clk32();
  return c;
}
__device__ __forceinline__ uint2 timer_edge() {
  uint32_t g0, g;
  int n = 0;
  asm volatile("mov.u32 %0, %%globaltimer_lo;" : "=r"(g0)::"memory");
#pragma unroll 1
  do { asm volatile("mov.u32 %0, %%globaltimer_lo;" : "=r"(g)::"memory"); } while (g == g0 && ++n < 8);
  return make_uint2(g, clk32());
}
__device__ __forceinline__ float4 lds_f4(uint32_t a) {
  float4 v;
  asm volatile("ld.shared.v4.f32 {%0,%1,%2,%3}, [%4];" : "=f"(v.x), "=f"(v.y), "=f"(v.z), "=f"(v.w) : "r"(a) : "memory");
  return v;
}
__device__ __forceinline__ uint4 lds_u4(uint32_t a) {
  uint4 v;
  asm volatile("ld.shared.v4.u32 {%0,%1,%2,%3}, [%4];" : "=r"(v.x), "=r"(v.y), "=r"(v.z), "=r"(v.w) : "r"(a) : "memory");
  return v;
}
__device__ __forceinline__ uint2 lds_u2(uint32_t a) {
  uint2 v;
  asm volatile("ld.shared.v2.u32 {%0,%1}, [%2];" : "=r"(v.x), "=r"(v.y) : "r"(a) : "memory");
  return v;
}
__device__ __forceinline__ uint32_t lds_u1(uint32_t a) {
  uint32_t v;
  asm volatile("ld.shared.u32 %0, [%1];" : "=r"(v) : "r"(a) : "memory");
  return v;
}
__device__ __forceinline__ void sts_u4(uint32_t a, uint4 v) {
  asm volatile("st.shared.v4.u32 [%0], {%1,%2,%3,%4};" ::"r"(a), "r"(v.x), "r"(v.y), "r"(v.z), "r"(v.w) : "memory");
}
__device__ __forceinline__ void sts_f4(uint32_t a, const float* d) {
  asm volatile("st.shared.v4.f32 [%0], {%1,%2,%3,%4};" ::"r"(a), "f"(d[0]), "f"(d[1]), "f"(d[2]), "f"(d[3]) : "memory");
}
__device__ __forceinline__ void sts_u2(uint32_t a, uint32_t x, uint32_t y) {
  asm volatile("st.shared.v2.u32 [%0], {%1,%2};" ::"r"(a), "r"(x), "r"(y) : "memory");
}
__device__ __forceinline__ void sts_u1(uint32_t a, uint32_t v) {
  asm volatile("st.shared.u32 [%0], %1;" ::"r"(a), "r"(v) : "memory");
}
__device__ __forceinline__ void sta4(uint32_t a, uint4 v, uint32_t bar) {
  asm volatile("st.async.shared::cluster.mbarrier::complete_tx::bytes.v4.b32 [%0], {%1,%2,%3,%4}, [%5];"
               ::"r"(a), "r"(v.x), "r"(v.y), "r"(v.z), "r"(v.w), "r"(bar) : "memory");
}
__device__ __forceinline__ void sta2(uint32_t a, uint32_t x, uint32_t y, uint32_t bar) {
  asm volatile("st.async.shared::cluster.mbarrier::complete_tx::bytes.v2.b32 [%0], {%1,%2}, [%3];" ::"r"(a), "r"(x), "r"(y), "r"(bar) : "memory");
}
__device__ __forceinline__ void sta1(uint32_t a, uint32_t x, uint32_t bar) {
  asm volatile("st.async.shared::cluster.mbarrier::complete_tx::bytes.b32 [%0], %1, [%2];" ::"r"(a), "r"(x), "r"(bar) : "memory");
}
__device__ __forceinline__ void arrive_remote(uint32_t bar) {
  asm volatile("mbarrier.arrive.shared::cluster.b64 _, [%0];" ::"r"(bar) : "memory");
}
__device__ __forceinline__ uint32_t peer_base(uint32_t sb, int rank) {
  uint32_t r;
  asm("mapa.shared::cluster.u32 %0, %1, %2;" : "=r"(r) : "r"(sb), "r"(rank));
  return r - sb;
}
__device__ __forceinline__ float ex2(float x) { float r; asm("ex2.approx.ftz.f32 %0, %1;" : "=f"(r) : "f"(x)); return r; }
__device__ __forceinline__ float rcp(float x) { float r; asm("rcp.approx.ftz.f32 %0, %1;" : "=f"(r) : "f"(x)); return r; }
__device__ __forceinline__ uint32_t min4(uint4 v) { return min(__vimin3_u32(v.x, v.y, v.z), v.w); }

__device__ __forceinline__ void softmax_e(float* sc) {
  float mx = fmaxf(fmaxf(fmaxf(sc[0], sc[1]), fmaxf(sc[2], sc[3])), fmaxf(fmaxf(sc[4], sc[5]), fmaxf(sc[6], sc[7])));
  mx = fmaxf(mx, fmaxf(sc[8], sc[9]));
  const float m1 = __shfl_xor_sync(~0u, mx, 1), m2 = __shfl_xor_sync(~0u, mx, 2), m3 = __shfl_xor_sync(~0u, mx, 3);
  mx = fmaxf(fmaxf(mx, m1), fmaxf(m2, m3));
  const float c = 0.08838834764831845f * 1.4426950408889634f, mc = -mx * c;
#pragma unroll
  for (int i = 0; i < 10; i++) sc[i] = ex2(fmaf(sc[i], c, mc));
}
__device__ __forceinline__ void sum_scores(float* sc, uint2 u0, uint2 u1, uint32_t u2, uint2 v0, uint2 v1, uint32_t v2) {
  sc[0] = bf_lo(u0.x) + bf_lo(v0.x); sc[1] = bf_hi(u0.x) + bf_hi(v0.x);
  sc[2] = bf_lo(u0.y) + bf_lo(v0.y); sc[3] = bf_hi(u0.y) + bf_hi(v0.y);
  sc[4] = bf_lo(u1.x) + bf_lo(v1.x); sc[5] = bf_hi(u1.x) + bf_hi(v1.x);
  sc[6] = bf_lo(u1.y) + bf_lo(v1.y); sc[7] = bf_hi(u1.y) + bf_hi(v1.y);
  sc[8] = bf_lo(u2) + bf_lo(v2); sc[9] = bf_hi(u2) + bf_hi(v2);
}
__device__ __forceinline__ void pv_mma(float* o0, float* o1, float* sm, const uint4* vx, const uint2* m, const uint32_t* p) {
  const uint32_t one = 0x3F803F80u;
#pragma unroll
  for (int i = 0; i < 4; i++) o0[i] = o1[i] = sm[i] = 0.f;
  mma16816(sm, one, one, one, one, p[0], p[1]);
  mma16816(o0, vx[0].x, vx[0].y, vx[0].z, vx[0].w, p[0], p[1]);
  mma16816(o1, vx[1].x, vx[1].y, vx[1].z, vx[1].w, p[0], p[1]);
  mma16816(sm, one, one, one, one, p[2], p[3]);
  mma16816(o0, vx[2].x, vx[2].y, vx[2].z, vx[2].w, p[2], p[3]);
  mma16816(o1, vx[3].x, vx[3].y, vx[3].z, vx[3].w, p[2], p[3]);
  mma1688(sm, one, one, p[4]);
  mma16816(o0, m[0].x, m[0].y, m[1].x, m[1].y, p[4], p[4]);
  mma16816(o1, m[2].x, m[2].y, m[3].x, m[3].y, p[4], p[4]);
}
#define D16(d) "+f"(d[0]), "+f"(d[1]), "+f"(d[2]), "+f"(d[3]), "+f"(d[4]), "+f"(d[5]), "+f"(d[6]), "+f"(d[7]), "+f"(d[8]), \
               "+f"(d[9]), "+f"(d[10]), "+f"(d[11]), "+f"(d[12]), "+f"(d[13]), "+f"(d[14]), "+f"(d[15])
__device__ __forceinline__ void wgmma_rs32(float* d, const uint32_t* a, uint64_t b, int scale_d) {
  asm volatile(
      "{.reg .pred p; setp.ne.b32 p, %21, 0;\n"
      "wgmma.mma_async.sync.aligned.m64n32k16.f32.bf16.bf16 {%0,%1,%2,%3,%4,%5,%6,%7,%8,%9,%10,%11,%12,%13,%14,%15}, "
      "{%16,%17,%18,%19}, %20, p, 1, 1, 0;}"
      : D16(d) : "r"(a[0]), "r"(a[1]), "r"(a[2]), "r"(a[3]), "l"(b), "r"(scale_d));
}
__device__ __forceinline__ void wgmma_ss32(float* d, uint64_t a, uint64_t b, int scale_d) {
  asm volatile(
      "{.reg .pred p; setp.ne.b32 p, %18, 0;\n"
      "wgmma.mma_async.sync.aligned.m64n32k16.f32.bf16.bf16 {%0,%1,%2,%3,%4,%5,%6,%7,%8,%9,%10,%11,%12,%13,%14,%15}, "
      "%16, %17, p, 1, 1, 1, 0;}"
      : D16(d) : "l"(a), "l"(b), "r"(scale_d));
}
#define R32 "{%0,%1,%2,%3,%4,%5,%6,%7,%8,%9,%10,%11,%12,%13,%14,%15,%16,%17,%18,%19,%20,%21,%22,%23,%24,%25,%26,%27,%28,%29,%30,%31}, "
__device__ __forceinline__ void wgmma_rs64(float* d, const uint32_t* a, uint64_t b, int scale_d) {
  asm volatile("{.reg .pred p; setp.ne.b32 p, %37, 0;\nwgmma.mma_async.sync.aligned.m64n64k16.f32.bf16.bf16 " R32 "{%32,%33,%34,%35}, %36, p, 1, 1, 0;}"
               : D16(d), D16((d + 16)) : "r"(a[0]), "r"(a[1]), "r"(a[2]), "r"(a[3]), "l"(b), "r"(scale_d));
}
__device__ __forceinline__ void wgmma_ss64(float* d, uint64_t a, uint64_t b) {
  asm volatile("wgmma.mma_async.sync.aligned.m64n64k16.f32.bf16.bf16 " R32 "%32, %33, 1, 1, 1, 1, 0;" : D16(d), D16((d + 16)) : "l"(a), "l"(b));
}
__device__ __forceinline__ void wgmma_ss48(float* d, uint64_t a, uint64_t b, int scale_d) {
  asm volatile(
      "{.reg .pred p; setp.ne.b32 p, %26, 0;\n"
      "wgmma.mma_async.sync.aligned.m64n48k16.f32.bf16.bf16 {%0,%1,%2,%3,%4,%5,%6,%7,%8,%9,%10,%11,%12,%13,%14,%15,"
      "%16,%17,%18,%19,%20,%21,%22,%23}, %24, %25, p, 1, 1, 0, 0;}"
      : D16(d), "+f"(d[16]), "+f"(d[17]), "+f"(d[18]), "+f"(d[19]), "+f"(d[20]), "+f"(d[21]), "+f"(d[22]), "+f"(d[23])
      : "l"(a), "l"(b), "r"(scale_d));
}
enum { T_W1, T_W2, T_W3, T_W4, T_WO, T_LN };
constexpr int NPAIR = 18, G_STAGES = 4, G_STAGE_BYTES = 49152, G_STG = G_STAGES * G_STAGE_BYTES, G_BAR = G_STG + 32768,
              G_SMEM = G_BAR + 512;
constexpr int WAIT_LIM = 1 << 22;
#define NSLP 40
enum { C_H1 = 0, C_LN1 = 16, C_H3 = 32, C_G = 48, C_OX = 64, C_LN = 128, C_CHK, C_DONE, C_END };
__device__ __align__(128) unsigned g_cnt[C_END * 8];

struct GemmMaps { CUtensorMap a[5], b[5], c[6], e[4], od; };
__constant__ unsigned short c_list[2 * NPAIR][24] = {
    {0x1130, 0x1160, 0x121, 0xd1, 0x612, 0x132, 0x5f2, 0x352, 0x252, 0xf2, 0x3d2, 0x43, 0xe3, 0x873, 0x8000, 0x8000, 0x8000, 0x8000, 0x8000, 0x8000, 0x8000, 0x8000, 0x8000, 0x30},
    {0x1138, 0x1168, 0x129, 0xd9, 0x61a, 0x13a, 0x5fa, 0x35a, 0x25a, 0xfa, 0x3da, 0x4b, 0xeb, 0x87b, 0x8000, 0x8000, 0x8000, 0x8000, 0x8000, 0x8000, 0x8000, 0x8000, 0x8000, 0x30},
    {0x1120, 0x9c0, 0x1b1, 0x492, 0x602, 0x682, 0x4a2, 0x372, 0x362, 0x162, 0xb3, 0x63, 0x2944, 0x8000, 0x8000, 0x8000, 0x8000, 0x8000, 0x8000, 0x8000, 0x8000, 0x8000, 0x8000, 0x30},
    {0x1128, 0x9c8, 0x1b9, 0x49a, 0x60a, 0x68a, 0x4aa, 0x37a, 0x36a, 0x16a, 0xbb, 0x6b, 0x29c4, 0x8000, 0x8000, 0x8000, 0x8000, 0x8000, 0x8000, 0x8000, 0x8000, 0x8000, 0x8000, 0x30},
    {0xd0, 0x1050, 0x101, 0x1c1, 0x12, 0x3a2, 0x6c2, 0x2b2, 0x1c2, 0x4d2, 0x13, 0xb4, 0x2954, 0x8000, 0x8000, 0x8000, 0x8000, 0x8000, 0x8000, 0x8000, 0x8000, 0x8000, 0x8000, 0x30},
    {0xd8, 0x1058, 0x109, 0x1c9, 0x1a, 0x3aa, 0x6ca, 0x2ba, 0x1ca, 0x4da, 0x1b, 0xbc, 0x29d4, 0x8000, 0x8000, 0x8000, 0x8000, 0x8000, 0x8000, 0x8000, 0x8000, 0x8000, 0x8000, 0x30},
    {0x1030, 0x840, 0x131, 0x192, 0x22, 0x632, 0x4b2, 0x3c2, 0x72, 0x3e2, 0x23, 0x1e3, 0x994, 0x8000, 0x8000, 0x8000, 0x8000, 0x8000, 0x8000, 0x8000, 0x8000, 0x8000, 0x8000, 0x30},
    {0x1038, 0x848, 0x139, 0x19a, 0x2a, 0x63a, 0x4ba, 0x3ca, 0x7a, 0x3ea, 0x2b, 0x1eb, 0x99c, 0x8000, 0x8000, 0x8000, 0x8000, 0x8000, 0x8000, 0x8000, 0x8000, 0x8000, 0x8000, 0x30},
    {0x11b0, 0x11f0, 0x1a1, 0x161, 0x92, 0x82, 0x4e2, 0x342, 0x42, 0x6e2, 0x103, 0x184, 0x914, 0x8000, 0x8000, 0x8000, 0x8000, 0x8000, 0x8000, 0x8000, 0x8000, 0x8000, 0x8000, 0x30},
    {0x11b8, 0x11f8, 0x1a9, 0x169, 0x9a, 0x8a, 0x4ea, 0x34a, 0x4a, 0x6ea, 0x10b, 0x18c, 0x91c, 0x8000, 0x8000, 0x8000, 0x8000, 0x8000, 0x8000, 0x8000, 0x8000, 0x8000, 0x8000, 0x30},
    {0x1190, 0x1170, 0x21, 0xe1, 0x392, 0x1b2, 0x442, 0x6b2, 0x642, 0x4f2, 0x113, 0x134, 0x8a4, 0x8000, 0x8000, 0x8000, 0x8000, 0x8000, 0x8000, 0x8000, 0x8000, 0x8000, 0x8000, 0x30},
    {0x1198, 0x1178, 0x29, 0xe9, 0x39a, 0x1ba, 0x44a, 0x6ba, 0x64a, 0x4fa, 0x11b, 0x13c, 0x8ac, 0x8000, 0x8000, 0x8000, 0x8000, 0x8000, 0x8000, 0x8000, 0x8000, 0x8000, 0x8000, 0x30},
    {0x1090, 0x8c0, 0x31, 0xf1, 0xa2, 0x3b2, 0x322, 0x262, 0x662, 0x572, 0x33, 0xd3, 0x884, 0x8000, 0x8000, 0x8000, 0x8000, 0x8000, 0x8000, 0x8000, 0x8000, 0x8000, 0x8000, 0x30},
    {0x1098, 0x8c8, 0x39, 0xf9, 0xaa, 0x3ba, 0x32a, 0x26a, 0x66a, 0x57a, 0x3b, 0xdb, 0x88c, 0x8000, 0x8000, 0x8000, 0x8000, 0x8000, 0x8000, 0x8000, 0x8000, 0x8000, 0x8000, 0x30},
    {0x1180, 0x950, 0xb1, 0x171, 0x222, 0x412, 0x432, 0x482, 0x472, 0x2e2, 0x123, 0x1a3, 0x894, 0x8000, 0x8000, 0x8000, 0x8000, 0x8000, 0x8000, 0x8000, 0x8000, 0x8000, 0x8000, 0x30},
    {0x1188, 0x958, 0xb9, 0x179, 0x22a, 0x41a, 0x43a, 0x48a, 0x47a, 0x2ea, 0x12b, 0x1ab, 0x89c, 0x8000, 0x8000, 0x8000, 0x8000, 0x8000, 0x8000, 0x8000, 0x8000, 0x8000, 0x8000, 0x30},
    {0x8b0, 0x891, 0x61, 0x202, 0x382, 0x332, 0x62, 0x3f2, 0x672, 0x3, 0xc3, 0x284c, 0x8000, 0x8000, 0x8000, 0x8000, 0x8000, 0x8000, 0x8000, 0x8000, 0x8000, 0x8000, 0x8000, 0x30},
    {0x8b8, 0x899, 0x69, 0x20a, 0x38a, 0x33a, 0x6a, 0x3fa, 0x67a, 0xb, 0xcb, 0x28cc, 0x8000, 0x8000, 0x8000, 0x8000, 0x8000, 0x8000, 0x8000, 0x8000, 0x8000, 0x8000, 0x8000, 0x30},
    {0x820, 0x991, 0x71, 0x2a2, 0x5b2, 0x1e2, 0x232, 0x1d2, 0x6f2, 0xa3, 0x163, 0x2854, 0x8000, 0x8000, 0x8000, 0x8000, 0x8000, 0x8000, 0x8000, 0x8000, 0x8000, 0x8000, 0x8000, 0x30},
    {0x828, 0x999, 0x79, 0x2aa, 0x5ba, 0x1ea, 0x23a, 0x1da, 0x6fa, 0xab, 0x16b, 0x28d4, 0x8000, 0x8000, 0x8000, 0x8000, 0x8000, 0x8000, 0x8000, 0x8000, 0x8000, 0x8000, 0x8000, 0x30},
    {0x880, 0x811, 0x1e1, 0x522, 0x32, 0x102, 0x1a2, 0xd2, 0x52, 0x83, 0x53, 0x294c, 0x8000, 0x8000, 0x8000, 0x8000, 0x8000, 0x8000, 0x8000, 0x8000, 0x8000, 0x8000, 0x8000, 0x30},
    {0x888, 0x819, 0x1e9, 0x52a, 0x3a, 0x10a, 0x1aa, 0xda, 0x5a, 0x8b, 0x5b, 0x29cc, 0x8000, 0x8000, 0x8000, 0x8000, 0x8000, 0x8000, 0x8000, 0x8000, 0x8000, 0x8000, 0x8000, 0x30},
    {0x810, 0x911, 0x1f1, 0x182, 0x122, 0x242, 0x5e2, 0x5d2, 0x552, 0x183, 0xf3, 0x2844, 0x8000, 0x8000, 0x8000, 0x8000, 0x8000, 0x8000, 0x8000, 0x8000, 0x8000, 0x8000, 0x8000, 0x30},
    {0x818, 0x919, 0x1f9, 0x18a, 0x12a, 0x24a, 0x5ea, 0x5da, 0x55a, 0x18b, 0xfb, 0x28c4, 0x8000, 0x8000, 0x8000, 0x8000, 0x8000, 0x8000, 0x8000, 0x8000, 0x8000, 0x8000, 0x8000, 0x30},
    {0x1000, 0x1060, 0xa1, 0x51, 0x212, 0x302, 0x6d2, 0x422, 0x4c2, 0x152, 0x133, 0x1b4, 0x924, 0x8000, 0x8000, 0x8000, 0x8000, 0x8000, 0x8000, 0x8000, 0x8000, 0x8000, 0x8000, 0x30},
    {0x1008, 0x1068, 0xa9, 0x59, 0x21a, 0x30a, 0x6da, 0x42a, 0x4ca, 0x15a, 0x13b, 0x1bc, 0x92c, 0x8000, 0x8000, 0x8000, 0x8000, 0x8000, 0x8000, 0x8000, 0x8000, 0x8000, 0x8000, 0x30},
    {0x11a0, 0x1070, 0x81, 0x151, 0x592, 0x532, 0x622, 0xb2, 0x452, 0x462, 0x1b3, 0x34, 0x824, 0x8000, 0x8000, 0x8000, 0x8000, 0x8000, 0x8000, 0x8000, 0x8000, 0x8000, 0x8000, 0x30},
    {0x11a8, 0x1078, 0x89, 0x159, 0x59a, 0x53a, 0x62a, 0xba, 0x45a, 0x46a, 0x1bb, 0x3c, 0x82c, 0x8000, 0x8000, 0x8000, 0x8000, 0x8000, 0x8000, 0x8000, 0x8000, 0x8000, 0x8000, 0x30},
    {0x900, 0x8e0, 0x141, 0x512, 0x2, 0x282, 0x2f2, 0x172, 0xe2, 0x2d2, 0x143, 0x1d3, 0x804, 0x8000, 0x8000, 0x8000, 0x8000, 0x8000, 0x8000, 0x8000, 0x8000, 0x8000, 0x8000, 0x30},
    {0x908, 0x8e8, 0x149, 0x51a, 0xa, 0x28a, 0x2fa, 0x17a, 0xea, 0x2da, 0x14b, 0x1db, 0x80c, 0x8000, 0x8000, 0x8000, 0x8000, 0x8000, 0x8000, 0x8000, 0x8000, 0x8000, 0x8000, 0x30},
    {0x1110, 0x9d0, 0x41, 0x312, 0x692, 0x5a2, 0x142, 0xc2, 0x652, 0x1f2, 0x1c3, 0x153, 0x9a4, 0x8000, 0x8000, 0x8000, 0x8000, 0x8000, 0x8000, 0x8000, 0x8000, 0x8000, 0x8000, 0x30},
    {0x1118, 0x9d8, 0x49, 0x31a, 0x69a, 0x5aa, 0x14a, 0xca, 0x65a, 0x1fa, 0x1cb, 0x15b, 0x9ac, 0x8000, 0x8000, 0x8000, 0x8000, 0x8000, 0x8000, 0x8000, 0x8000, 0x8000, 0x8000, 0x30},
    {0x140, 0x11e0, 0x181, 0xc1, 0x292, 0x502, 0x6a2, 0x402, 0x272, 0x93, 0x104, 0x14, 0x295c, 0x8000, 0x8000, 0x8000, 0x8000, 0x8000, 0x8000, 0x8000, 0x8000, 0x8000, 0x8000, 0x40},
    {0x148, 0x11e8, 0x189, 0xc9, 0x29a, 0x50a, 0x6aa, 0x40a, 0x27a, 0x9b, 0x10c, 0x1c, 0x29dc, 0x8000, 0x8000, 0x8000, 0x8000, 0x8000, 0x8000, 0x8000, 0x8000, 0x8000, 0x8000, 0x40},
    {0x10a0, 0x10f0, 0x1, 0x1d1, 0x112, 0x582, 0x542, 0x5c2, 0x2c2, 0x562, 0x193, 0x1f3, 0x173, 0x285c, 0x8000, 0x8000, 0x8000, 0x8000, 0x8000, 0x8000, 0x8000, 0x8000, 0x8000, 0x40},
    {0x10a8, 0x10f8, 0x9, 0x1d9, 0x11a, 0x58a, 0x54a, 0x5ca, 0x2ca, 0x56a, 0x19b, 0x1fb, 0x17b, 0x28dc, 0x8000, 0x8000, 0x8000, 0x8000, 0x8000, 0x8000, 0x8000, 0x8000, 0x8000, 0x40},
};
struct Tile { int valid, ty, mt, nt, flush, nkb, wide; };
__device__ __forceinline__ Tile decode(int v) {
  Tile t;
  t.valid = v < 0x8000; t.ty = v & 7; t.mt = (v >> 3) & 15; t.nt = (v >> 7) & 15; t.flush = (v >> 11) & 3; t.wide = v & 0x2000;
  t.nkb = t.ty == T_W4 ? 56 : (t.ty == T_WO ? 64 : 16);
  return t;
}
__device__ __forceinline__ unsigned ld_acq(int c) {
  unsigned v;
  asm volatile("ld.acquire.gpu.global.u32 %0, [%1];" : "=r"(v) : "l"(g_cnt + c * 8) : "memory");
  return v;
}
__device__ __forceinline__ void wait_cnt(int c, unsigned target) {
  unsigned v;
  int n = 0;
#pragma unroll 1
  do {
    v = ld_acq(c);
    if (v >= target) break;
    __nanosleep(NSLP);
  } while (++n < WAIT_LIM);
}
__device__ __forceinline__ void sig_cnt(int c, int v = 1) {
  asm volatile("red.release.gpu.global.add.u32 [%0], %1;" ::"l"(g_cnt + c * 8), "r"(v) : "memory");
}
__device__ __forceinline__ void fence_async_all() { asm volatile("fence.proxy.async.global;" ::: "memory"); }
__device__ __forceinline__ void arrive_both(uint32_t bar) {
  asm volatile(
      "{.reg .b32 r0, r1; mapa.shared::cluster.u32 r0, %0, 0; mapa.shared::cluster.u32 r1, %0, 1;\n"
      "mbarrier.arrive.shared::cluster.b64 _, [r0];\n"
      "mbarrier.arrive.shared::cluster.b64 _, [r1];}" ::"r"(bar) : "memory");
}
__device__ __forceinline__ void load_b(uint32_t dst, const CUtensorMap* m, int k, int ng, uint32_t bar) {
  asm volatile(
      "cp.async.bulk.tensor.3d.shared::cluster.global.mbarrier::complete_tx::bytes.multicast::cluster [%0], [%1, {%3, %4, %5}], [%2], %6;"
      ::"r"(dst), "l"(m), "r"(bar), "r"(0), "r"(k), "r"(ng), "h"((uint16_t)3) : "memory");
}
__device__ __forceinline__ float gelu_f(float x) {
  float u = x * (0.7978845608f + 0.0356774081f * x * x), t;
  asm("tanh.approx.f32 %0, %1;" : "=f"(t) : "f"(u));
  return fmaf(x, t, x);
}
__device__ __forceinline__ float silu_f(float x) {
  float hx = 0.5f * x, t;
  asm("tanh.approx.f32 %0, %1;" : "=f"(t) : "f"(hx));
  return fmaf(hx, t, hx);
}

__device__ __forceinline__ uint32_t add2(uint32_t a, uint32_t b) { uint32_t r; asm("add.rn.bf16x2 %0, %1, %2;" : "=r"(r) : "r"(a), "r"(b)); return r; }
__device__ __forceinline__ uint32_t mul2(uint32_t a, uint32_t b) { uint32_t r; asm("mul.rn.bf16x2 %0, %1, %2;" : "=r"(r) : "r"(a), "r"(b)); return r; }
__device__ __forceinline__ uint32_t fma2(uint32_t a, uint32_t b, uint32_t c) { uint32_t r; asm("fma.rn.bf16x2 %0, %1, %2, %3;" : "=r"(r) : "r"(a), "r"(b), "r"(c)); return r; }

__device__ __forceinline__ uint32_t scale2(uint32_t d, uint32_t hi, uint32_t lo) {
  uint32_t r;
  asm("fma.rn.bf16x2 %0, %1, %2, %3;" : "=r"(r) : "r"(d), "r"(hi), "r"(mul2(d, lo)));
  return r;
}
__device__ __forceinline__ void split2(float s, uint32_t& hi, uint32_t& lo) {
  hi = pack_bf16(s, s);
  const float r = s - bf_lo(hi);
  lo = pack_bf16(r, r);
}
__device__ __forceinline__ float ln_inv(float m2) {
  float sd, inv;
  asm("sqrt.approx.f32 %0, %1;" : "=f"(sd) : "f"(rbf(rbf(m2 * (1.f / 1024.f)) + 1e-5f)));
  asm("rcp.approx.f32 %0, %1;" : "=f"(inv) : "f"(rbf(sd)));
  return inv;
}
__device__ __forceinline__ void ln_packed(uint32_t* u) {
  float s = 0.f, s2 = 0.f;
#pragma unroll
  for (int i = 0; i < 16; i++) { s += bf_lo(u[i]); s2 += bf_hi(u[i]); }
  s += s2;
#pragma unroll
  for (int o = 16; o > 0; o >>= 1) s += __shfl_xor_sync(~0u, s, o);
  float mean = s * (1.f / 1024.f), q = 0.f, q2 = 0.f;
#pragma unroll
  for (int i = 0; i < 16; i++) { float a = bf_lo(u[i]) - mean, b = bf_hi(u[i]) - mean; q = fmaf(a, a, q); q2 = fmaf(b, b, q2); }
  q += q2;
#pragma unroll
  for (int o = 16; o > 0; o >>= 1) q += __shfl_xor_sync(~0u, q, o);
  const uint32_t nmb = pack_bf16(-mean, -mean);
  uint32_t hi, lo;
  split2(ln_inv(q), hi, lo);
#pragma unroll
  for (int i = 0; i < 16; i++) u[i] = scale2(add2(u[i], nmb), hi, lo);
}
__device__ __forceinline__ void row_ld(uint32_t* u, const bf16* p, int lane) {
#pragma unroll
  for (int i = 0; i < 4; i++) {
    uint4 v = __ldcg((const uint4*)(p + i * 256 + lane * 8));
    u[i * 4] = v.x; u[i * 4 + 1] = v.y; u[i * 4 + 2] = v.z; u[i * 4 + 3] = v.w;
  }
}
__device__ __forceinline__ void row_st(const uint32_t* u, bf16* p, int lane) {
#pragma unroll
  for (int i = 0; i < 4; i++) *(uint4*)(p + i * 256 + lane * 8) = make_uint4(u[i * 4], u[i * 4 + 1], u[i * 4 + 2], u[i * 4 + 3]);
}

template <int N>
__device__ __forceinline__ void activate(uint32_t* pk, int act) {
  if (act == T_W1 || act == T_W3) {
#pragma unroll
    for (int i = 0; i < N; i++) pk[i] = pack_bf16(gelu_f(bf_lo(pk[i])), gelu_f(bf_hi(pk[i])));
  } else if (act == T_W4) {
#pragma unroll
    for (int i = 0; i < N; i++) pk[i] = pack_bf16(silu_f(bf_lo(pk[i])), silu_f(bf_hi(pk[i])));
  }
}
__device__ __forceinline__ void epi_store(const uint32_t* pk, uint32_t bf, uint32_t xo, const CUtensorMap* cm, int col, int row, int lane) {
  if (lane == 0) asm volatile("cp.async.bulk.wait_group.read 1;" ::: "memory");
  __syncwarp();
#pragma unroll
  for (int q = 0; q < 4; q++) stsm4(bf + (xo ^ (q << 5)), pk[q * 4], pk[q * 4 + 1], pk[q * 4 + 2], pk[q * 4 + 3]);
  fence_async_smem();
  __syncwarp();
  if (lane == 0) {
    tma_store_2d(cm, bf, col, row);
    asm volatile("cp.async.bulk.commit_group;" ::: "memory");
  }
}

#define DP0 3
#define DPK 4
#define DPS 1
#define NA0 5
#define NA1 11
#define PP 3
#define DQ 2
constexpr int NRD = 5, D_STAGES = 5, D_W = 0, D_RING = 2 * (8 - NRD) * 16384, D_SUM = D_RING + 5 * 16384;
static_assert(D_SUM + 16384 <= G_STG, "smem");
__device__ constexpr int d_head(int i) { return i < DQ ? i : (i < DQ + 8 - NRD ? i + NRD - DQ : i - 8 + NRD); }

__global__ void __cluster_dims__(2, 1, 1) __launch_bounds__(384, 1)
k_gemm(const __grid_constant__ GemmMaps maps, const bf16* __restrict__ x, bf16* __restrict__ out) {
  extern __shared__ __align__(1024) unsigned char smem_raw[];
  const uint32_t sb = smem_u32(smem_raw);
  const int tid = threadIdx.x, wid = __shfl_sync(~0u, tid >> 5, 0), wg = wid >> 2, w = wid & 3, lane = tid & 31;
  const int rank = blockIdx.x & 1, cl = blockIdx.x >> 1;
  const uint32_t bFull = sb + G_BAR, bEmpty = bFull + 32, bPub = bFull + 64, dFull = bFull + 72, dEmpty = dFull + 48, dW = dEmpty + 48, dReady = dW + 8,
                 xF = bFull + 256, xE = xF + 64;
  const int dq = blockIdx.x & 3;
  if (tid >= 32 && tid < 32 + 21) asm volatile("prefetch.tensormap [%0];" ::"l"(&maps.a[0] + (tid - 32)) : "memory");
  if (tid == 0) {
    TG(95, 0);
    if (sb & 1023) __trap();
    for (int i = 0; i < G_STAGES; i++) { mbar_init(bFull + i * 8, 1); mbar_init(bEmpty + i * 8, 4); }
    for (int i = 0; i < D_STAGES; i++) { mbar_init(dFull + i * 8, 1); mbar_init(dEmpty + i * 8, 2); }
    for (int i = 0; i < 16; i++) mbar_init(xF + i * 8, 1);
    mbar_init(dW, 1);
    mbar_init(bPub, 8);
    sts_u1(dReady, 0);
    asm volatile("fence.mbarrier_init.release.cluster;" ::: "memory");
  }
  __syncthreads();
  asm volatile("barrier.cluster.arrive.relaxed.aligned;" ::: "memory");
  if (wg == 2) {
    asm volatile("setmaxnreg.dec.sync.aligned.u32 40;");
    asm volatile("barrier.cluster.wait.aligned;" ::: "memory");
    if (w == 0 && lane == 0) {
      int st = 0, ph = 1, pe = 0, pcol = 0, pmt = 0;
#define ELOAD(j)                                                                           \
  {                                                                                        \
    mbar_wait(bEmpty + st * 8, ph);                                                        \
    const uint32_t full = bFull + st * 8, sa = sb + st * G_STAGE_BYTES;                    \
    mbar_expect_tx(full, (pe - 2) * 16384);                                                \
    tma_load_2d(sa, &maps.e[pe * 2 - 5], pcol + (j) * 64, pmt * 128, full);                \
    if (pe == T_WO) tma_load_2d(sa + 16384, &maps.e[2], pcol + (j) * 64, pmt * 128, full); \
    if (++st == G_STAGES) { st = 0; ph ^= 1; }                                             \
  }
      for (int r = 0;; r++) {
        const Tile t = decode(c_list[blockIdx.x][r]);
        if (!t.valid) break;
        const int mt = t.mt;
        const CUtensorMap *am = &maps.a[t.ty], *bm = &maps.b[t.ty];
        if (r == 0) {
          for (int kb = 0; kb < G_STAGES; kb++) {
            mbar_expect_tx(bFull + kb * 8, G_STAGE_BYTES);
            load_b(sb + kb * G_STAGE_BYTES + 16384 + rank * 16384, bm, kb * 64, t.nt * 4 + rank * 2, bFull + kb * 8);
          }
        }
        if (t.ty == T_W1) wait_cnt(C_LN, 96);
        else if (t.ty == T_W2) { wait_cnt(C_H1 + mt, 4); if (mt > 0) wait_cnt(C_H1 + mt - 1, 4); if (mt < 15) wait_cnt(C_H1 + mt + 1, 4); }
        else if (t.ty == T_W3) wait_cnt(C_LN1 + mt, 4);
        else if (t.ty == T_W4) wait_cnt(C_H3 + mt, 14);
        else wait_cnt(C_OX + mt * 4 + 3, 128);
        if (pe == T_WO) wait_cnt(C_G + pmt, 4);
        fence_async_all();
        TG(r, 0);
        if (r == 0 && cl == 0) ST(5);
        for (int kb = 0; kb < t.nkb; kb++) {
          const bool early = r == 0 && kb < G_STAGES;
          if (pe && !(kb & ~12)) ELOAD(kb >> 2);
          if (kb >> 2 == 12) tma_prefetch_2d(&maps.e[t.ty * 2 - 5], t.nt * 256 + (kb & 3) * 64, mt * 128);
          mbar_wait(bEmpty + st * 8, ph);
          const uint32_t full = bFull + st * 8, sa = sb + st * G_STAGE_BYTES;
          if (!early) mbar_expect_tx(full, G_STAGE_BYTES);
          int roff = 0;
          if (t.ty == T_W2) { int gq = kb >> 2; roff = (gq & 1) ? (gq >> 1) + 1 : -((gq >> 1) + 1); }
          tma_load_2d(sa, am, kb * 64, mt * 128 + roff, full);
          if (t.wide) { tma_load_3d(sa + 16384, bm, 0, kb * 64, t.nt * 4, full); tma_load_3d(sa + 32768, bm, 0, kb * 64, t.nt * 4 + 2, full); }
          else if (!early) load_b(sa + 16384 + rank * 16384, bm, kb * 64, t.nt * 4 + rank * 2, full);
          if (++st == G_STAGES) { st = 0; ph ^= 1; }
        }
        pe = t.ty >= T_W4 ? t.ty : 0; pcol = t.nt * 256; pmt = mt;
        if (pe && t.flush) {
          if (pe == T_WO) { wait_cnt(C_G + mt, 4); fence_async_all(); }
          for (int j = 0; j < 4; j++) ELOAD(j);
          pe = 0;
        }
        for (int i = 0; i < (t.ty == T_W2 ? 2 : 0); i++) {
          mbar_wait(bEmpty + st * 8, ph);
          const uint32_t full = bFull + st * 8, sa = sb + st * G_STAGE_BYTES;
          mbar_expect_tx(full, 32768);
          tma_load_2d(sa, &maps.e[0], pcol + i * 128, mt * 128, full);
          tma_load_2d(sa + 16384, &maps.e[0], pcol + i * 128 + 64, mt * 128, full);
          if (++st == G_STAGES) { st = 0; ph ^= 1; }
        }
      }
      if (c_list[blockIdx.x][23] < NSEG) {
        mbar_expect_tx(dW, D_RING);
        for (int i = 0; i < G_STAGES; i++) {
          mbar_wait(bEmpty + st * 8, ph);
          for (int b = st * 3; b < min(st * 3 + 3, 11); b++) {
            const uint32_t bar = b < 6 ? dW : dFull + (b - 6) * 8;
            if (b > 5) mbar_expect_tx(bar, 16384);
            tma_load_3d(sb + b * 16384, &maps.b[T_WO], 0, dq * 1024 + (b < 5 ? b + 5 : b == 5 ? 15 : b - 6) * 64, cl & ~1, bar);
          }
          if (++st == G_STAGES) { st = 0; ph ^= 1; }
        }
      }
    } else if (w == 3 && lane == 0) {
      int ph = 0;
      for (int r = 0;; r++) {
        const Tile t = decode(c_list[blockIdx.x][r]);
        if (!t.valid) break;
        if (t.ty != T_WO) { mbar_wait_long(bPub, ph); ph ^= 1; sig_cnt(t.ty * 16 + t.mt); TG(r, 3); }
      }
    }
    __syncwarp();
    if (w < 3) bar_sync(3, 96);
    const int s0 = c_list[blockIdx.x][23];
    if (!(w & 1) && lane == 0 && s0 < NSEG) {
      int st = w >> 1, ph = 0, ready = s0;
      for (int n = st; n < 4 * (NSEG - s0); n += 2) {
        const int s = s0 + (n >> 3) * 2 + 1;
        if (s >= ready) {
#pragma unroll 1
          for (int it = 0; s >= ready && it < 64 * WAIT_LIM; it++)
            asm volatile("ld.acquire.cta.shared.u32 %0, [%1];" : "=r"(ready) : "r"(dReady) : "memory");
          fence_async_all();
          TG(24 + s, 0);
        }
        mbar_wait(dEmpty + st * 8, ph);
        const uint32_t full = dFull + st * 8, sa = sb + D_RING + st * 16384;
        if ((s | 2) == 51) TG(40 + (n & 7), s & 2);
        mbar_expect_tx(full, 16384);
        tma_load_3d(sa, &maps.od, 0, s * 32 - 32, dq * 16 + d_head(n & 7) * 2, full);
        if (n == 1) {
          mbar_expect_tx(dW, 5 * 16384);
          for (int q = 0; q < 5; q++) tma_load_3d(sb + D_W + q * 16384, &maps.b[T_WO], 0, dq * 1024 + NRD * 128 + q * 64, cl & ~1, dW);
        }
        if ((st += 2) >= D_STAGES) { st -= D_STAGES; ph ^= 1; }
      }
    } else if (w == 1) {
      int ready = s0;
#pragma unroll 1
      for (int it = 0; ready < NSEG; it++) {
        const int q = min(ready + (lane & 7), NSEG - 1);
        const bool ok = (lane < 16 && ld_acq(lane < 8 ? C_OX + q : C_G + (q >> 2)) >= (lane < 8 ? 128 : 4)) || it > WAIT_LIM;
        const uint32_t m = __ballot_sync(~0u, ok);
        const int n = __ffs(~(m & (m >> 8) & 255)) - 1;
        ready = min(ready + n, NSEG);
        __syncwarp();
        if (n == 0) __nanosleep(NSLP);
        else if (lane == 0) asm volatile("st.release.cta.shared.u32 [%0], %1;" ::"r"(dReady), "r"(ready) : "memory");
      }
      uint32_t last = 0;
      if (lane == 0) asm volatile("atom.acq_rel.gpu.global.inc.u32 %0, [%1], %2;" : "=r"(last) : "l"(g_cnt + C_DONE * 8), "r"(gridDim.x - 1) : "memory");
      if (__shfl_sync(~0u, last, 0) == gridDim.x - 1)
        for (int i = lane; i < C_DONE; i += 32) g_cnt[i * 8] = 0;
    }
    __syncwarp();
  } else {
    asm volatile("setmaxnreg.inc.sync.aligned.u32 232;");
    asm volatile("barrier.cluster.wait.aligned;" ::: "memory");
    const bool leader = (tid & 127) == 0;
    bool pubq = false;
    {
      const int rr = (lane & 7) + ((lane >> 3) & 1) * 8;
      const uint32_t sb = __shfl_sync(~0u, smem_u32(smem_raw), 0), bFull = sb + G_BAR, bEmpty = bFull + 32, bPub = bFull + 64;
      const uint32_t xo = __shfl_sync(~0u, rr * 128 + (((lane >> 4) ^ (rr & 7)) << 4), lane), buf = sb + G_STG + wid * 4096, erow = wid * 2048;
      int st = 0, ph = 0, r = 0, tv = c_list[blockIdx.x][0];
      uint32_t pk[64];
      int dact = -1, ecol = 0, drow = 0, done = 0, prev = 0;
      bool hold = false, flush = false, fast = false;
      const CUtensorMap* dcm = nullptr;
      float acc[128];
      if (PP && wg) bar_arrive(4, 256);
      while (true) {
        const Tile t = decode(tv);
        const int mt = t.mt;
        const bool run = t.valid && !hold;
#define KBLOCK(kb)                                                                                      \
  {                                                                                                     \
    mbar_wait(bFull + st * 8, ph);                                                                      \
    uint32_t sa = sb + st * G_STAGE_BYTES;                                                              \
    uint64_t da = make_desc(sa + wg * 8192, 16, 1024, 1), db = make_desc(sa + 16384, 8192, 1024, 1);    \
    if (PP) bar_sync(4 + wg, 256);                                                                      \
    WG_FENCE();                                                                                         \
    _Pragma("unroll") for (int k = 0; k < 4; k++) {                                                     \
      wgmma_n256(acc, da + k * 2, db + k * 128, ((kb) | k) != 0);                                       \
      if (k == PP - 1) bar_arrive(5 - wg, 256);                                                         \
    }                                                                                                   \
    WG_COMMIT();                                                                                        \
    if ((kb) > 0) { WG_WAIT(1); if (leader) arrive_both(bEmpty + prev * 8); }                           \
    prev = st;                                                                                          \
    if (++st == G_STAGES) { st = 0; ph ^= 1; }                                                          \
  }
#define PUBLISH()                                                                                       \
  {                                                                                                     \
    if (lane == 0) { asm volatile("cp.async.bulk.wait_group 0;" ::: "memory"); if (pubq) mbar_arrive(bPub); } \
    __syncwarp();                                                                                       \
    pubq = false;                                                                                       \
  }
#define EAPPLY(p, eb, OP)                                                                  \
  _Pragma("unroll") for (int q = 0; q < 4; q++) {                                          \
    uint32_t a[4];                                                                         \
    ldsm4(a, (eb) + (xo ^ (q << 5)));                                                      \
    _Pragma("unroll") for (int i = 0; i < 4; i++) (p)[q * 4 + i] = OP((p)[q * 4 + i], a[i]); \
  }
#define ADDH(a, b) fma2(a, dact == T_WO ? 0x3F803F80u : 0x3F003F00u, b)
        const bool eop = dact == T_W4 || dact == T_WO;
        const bool slow = run && !fast;
#pragma unroll
        for (int c = 0; c < 4; c++) {
          const int es = st, eph = ph;
          if (eop && ++st == G_STAGES) { st = 0; ph ^= 1; }
          if (run) KBLOCK(c ? c : done);
          if (run && c == 0 && tid == 0 && !done) TG(r, 1);
          if (eop) {
            mbar_wait(bFull + es * 8, eph);
            const uint32_t eb = sb + es * G_STAGE_BYTES + erow;
            if (dact == T_WO) EAPPLY(pk + c * 16, eb + 16384, mul2);
            EAPPLY(pk + c * 16, eb, ADDH);
            bar_sync(1 + wg, 128);
            if (leader) arrive_both(bEmpty + es * 8);
          }
          activate<NA0>(pk + c * 16, dact);
          if (slow) KBLOCK(1);
          activate<NA1 - NA0>(pk + c * 16 + NA0, dact);
          if (run) KBLOCK(1);
          activate<16 - NA1>(pk + c * 16 + NA1, dact);
          if (slow) KBLOCK(1);
          if (c == 0 && pubq) PUBLISH();
          if (dact >= 0) epi_store(pk + c * 16, buf + (c & 1) * 2048, xo, dcm, ecol + c * 64, drow, lane);
        }
        if (run) done += slow ? 16 : 8;
        if (dact == T_W2) {
          const uint2* sp = g_rstat + (drow + (lane >> 2)) * 4 + (lane & 3);
          uint2 q[2];
          for (int n = 0; n < WAIT_LIM; n++) {
            q[0] = ld_rlx2(sp); q[1] = ld_rlx2(sp + 32);
            if (!__any_sync(~0u, q[0].y == 0u || q[1].y == 0u)) break;
          }
          uint32_t nmb[2], hi[2], lo[2];
#pragma unroll
          for (int e = 0; e < 2; e++) {
            const float sp = __uint_as_float(q[e].x);
            float a = sp + __shfl_xor_sync(~0u, sp, 1);
            a += __shfl_xor_sync(~0u, a, 2);
            const float mean = a * (1.f / 1024.f), dm = sp * (1.f / 256.f) - mean;
            float v = fmaf(256.f * dm, dm, __uint_as_float(q[e].y & 0x7fffffffu));
            v += __shfl_xor_sync(~0u, v, 1);
            v += __shfl_xor_sync(~0u, v, 2);
            nmb[e] = pack_bf16(-mean, -mean);
            split2(ln_inv(v), hi[e], lo[e]);
          }
#pragma unroll
          for (int i = 0; i < 64; i++) pk[i] = scale2(add2(pk[i], nmb[i & 1]), hi[i & 1], lo[i & 1]);
          dact = T_LN;
          dcm = &maps.c[5];
          hold = flush;
          continue;
        }
        pubq = dact >= 0 && dact != T_WO;
        dact = -1;
        if (!run) {
          WG_WAIT(0);
          if (!t.valid) break;
          PUBLISH();
          hold = false;
          continue;
        }
        uint2* sp = g_rstat + (mt * 128 + wid * 16 + (lane >> 2)) * 4 + t.nt;
        if (t.ty == T_W4 && (lane & 3) == 0) { st_rlx2(sp, 0, 0); st_rlx2(sp + 32, 0, 0); }
        dact = t.ty; ecol = t.nt * 256; drow = mt * 128 + wid * 16; dcm = &maps.c[t.ty];
        flush = t.flush & 1; fast = t.flush || t.ty == T_W2; hold = flush || (t.flush && t.ty == T_W2);
        tv = c_list[blockIdx.x][++r];
#pragma unroll 1
        for (int kb = done; kb < t.nkb; kb++) {
          KBLOCK(1);
          if (kb == done + 1 && pubq) PUBLISH();
        }
        WG_WAIT(0);
        if (leader) arrive_both(bEmpty + prev * 8);
        if (tid == 0) TG(r - 1, 2);
#pragma unroll
        for (int i = 0; i < 64; i++) pk[i] = pack_bf16(acc[2 * i], acc[2 * i + 1]);
        done = 0;
        if (dact == T_W2) {
#pragma unroll
          for (int h = 0; h < 2; h++) {
            mbar_wait(bFull + st * 8, ph);
            const uint32_t eb = sb + st * G_STAGE_BYTES + erow;
            EAPPLY(pk + h * 32, eb, ADDH);
            EAPPLY(pk + h * 32 + 16, eb + 16384, ADDH);
            bar_sync(1 + wg, 128);
            if (leader) arrive_both(bEmpty + st * 8);
            if (++st == G_STAGES) { st = 0; ph ^= 1; }
          }
          const uint32_t one = 0x3F803F80u;
          float *sm = acc, *s2 = acc + 4, *q0 = acc + 8, *q1 = acc + 12;
#pragma unroll
          for (int i = 0; i < 32; i++) acc[i] = 0.f;
#pragma unroll
          for (int i = 0; i < 64; i += 4) mma16816((i & 4) ? s2 : sm, pk[i], pk[i + 1], pk[i + 2], pk[i + 3], one, one);
          sm[0] += s2[0]; sm[2] += s2[2];
          const uint32_t c0 = pack_bf16(sm[0] * (-1.f / 256.f), sm[0] * (-1.f / 256.f)), c1 = pack_bf16(sm[2] * (-1.f / 256.f), sm[2] * (-1.f / 256.f));
#pragma unroll
          for (int i = 0; i < 64; i += 4) {
            const uint32_t a0 = add2(pk[i], c0), a1 = add2(pk[i + 1], c1), a2 = add2(pk[i + 2], c0), a3 = add2(pk[i + 3], c1);
            mma16816(q0, a0, a1, a2, a3, a0, a2);
            mma16816(q1, a0, a1, a2, a3, a1, a3);
          }
          if ((lane >> 3) == (lane & 3)) {
            const float e0 = fmaf(sm[0], 1.f / 256.f, bf_lo(c0)), e1 = fmaf(sm[2], 1.f / 256.f, bf_lo(c1));
            const float m0 = fmaxf(fmaf(-256.f * e0, e0, (lane & 4) ? q0[1] : q0[0]), 0.f);
            const float m1 = fmaxf(fmaf(-256.f * e1, e1, (lane & 4) ? q1[3] : q1[2]), 0.f);
            st_rlx2(sp, __float_as_uint(sm[0]), __float_as_uint(m0) | 0x80000000u);
            st_rlx2(sp + 32, __float_as_uint(sm[2]), __float_as_uint(m1) | 0x80000000u);
          }
          __syncwarp();
        }
      }
    }
    if (tid == 0) { TG(95, 1); ST(8 + cl); }
    const int s0 = c_list[blockIdx.x][23];
    if (s0 < NSEG) {
      uint32_t W[NRD * 8][4];
      const uint32_t peer = peer_base(sb, rank ^ 1);
#define XFREE() if (lane == 0) { mbar_expect_tx(xF + wid * 8, 2048); arrive_remote(xE + wid * 8 + peer); }
      int st = 0, ph = 0;
      const uint32_t xw = sb + D_RING + wg * 8192 + ((lane >> 4) * 8 + (lane & 7)) * 128 + (((w * 2 + ((lane >> 3) & 1)) ^ (lane & 7)) << 4);
      mbar_wait(dW, 0);
#pragma unroll
      for (int k = 0; k < 20; k++) ldsm4t(W[20 + k], xw - D_RING + (k >> 2) * 16384 + (k & 3) * 2048);
#pragma unroll
      for (int i = 0; i < D_STAGES; i++) {
        mbar_wait(dFull + st * 8, ph);
#pragma unroll
        for (int k = 0; k < 4; k++) ldsm4t(W[i * 4 + k], xw + st * 16384 + k * 2048);
        bar_sync(1 + wg, 128);
        if (leader) mbar_arrive(dEmpty + st * 8);
        if (++st == D_STAGES) { st = 0; ph ^= 1; }
      }
      PUBLISH();
      XFREE();
      if (tid == 0) TG(95, 2);
      const uint32_t in = sb + G_STG + wid * 4096 + lane * 16, mine = (cl & 1) * 1024, keep = D_SUM - G_STG - wid * 2048;
      uint32_t dA = (uint32_t)make_desc(sb + D_W + wg * 8192, 1024, 1024, 1);
      const uint32_t dB = (uint32_t)make_desc(sb + D_RING, 16, 1024, 1);
      const uint32_t eb = (dq * 16 + (lane >> 2)) * D_ + (cl >> 1) * 128 + wid * 16 + (lane & 3) * 2, xb = blockIdx.x * 8192 + tid;
      int pend = 0, fin = 0;
#define SUM_LD(j) { a = lds_f4(in + (mine ^ (1024 - ((j) >> 1) * 1024)) + ((j) & 1) * 512); b = lds_f4(in + (mine ^ (1024 - ((j) >> 1) * 1024)) + ((j) & 1) * 512 + 2048); }
#define SUM_ST(j, on, u)                                                                                    \
  {                                                                                                      \
    const float c[4] = {a.x + b.x, a.y + b.y, a.z + b.z, a.w + b.w};                                     \
    if ((j) < 2)                                                                                         \
      asm volatile("{.reg .pred p; .reg .b128 r; setp.ne.b32 p, %5, 0; mov.b128 r, {%1,%2,%3,%4}; @p st.relaxed.gpu.global.b128 [%0], r;}" \
                   ::"l"(g_dx + (xb ^ 16384) + ((u) & 31) * 256 + (j) * 256), "r"(nz(asu(c[0]))), "r"(asu(c[1])), "r"(asu(c[2])), "r"(asu(c[3])), "r"(on) : "memory"); \
    else if (on) sts_f4(in + keep + ((u) & 2) * 512 + ((j) & 1) * 512, c);                                                 \
  }
#define OPERANDS(t, e)                                                                                   \
  {                                                                                                      \
    e[0] = ld_rlx1(g_gate + eo + t * 8 * D_); e[1] = ld_rlx1(g_gate + eo + t * 8 * D_ + 8);              \
    e[2] = __ldg((const uint32_t*)(x + eo + t * 8 * D_)); e[3] = __ldg((const uint32_t*)(x + eo + t * 8 * D_ + 8)); \
  }
#define RECV() { r = ld_rlx4(g_dx + xo); q = ld_rlx4(g_dx + xo + 256); }
#define CHECK() { for (int n = 0; (r.x == 0u || q.x == 0u) && n < WAIT_LIM; n++) RECV(); __syncwarp(); }
#define FIN_LD(on)                                                                                       \
  {                                                                                                      \
    if (on) { st_rlx4(g_dx + xo, 0, 0, 0, 0); st_rlx4(g_dx + xo + 256, 0, 0, 0, 0); }                    \
    a = lds_f4(in + keep + (u & 2) * 512); b = lds_f4(in + keep + (u & 2) * 512 + 512);                                                  \
  }
#define FIN_T(r, a)                                                                                      \
  {                                                                                                      \
    r.x = pack_bf16(a.x + asf(r.x), a.y + asf(r.y)); r.y = pack_bf16(a.z + asf(r.z), a.w + asf(r.w));    \
    asm volatile("movmatrix.sync.aligned.m8n8.trans.b16 %0, %0;" : "+r"(r.x));                           \
    asm volatile("movmatrix.sync.aligned.m8n8.trans.b16 %0, %0;" : "+r"(r.y));                           \
  }
#define FIN_ST(t, e, r, on)                                                                              \
  {                                                                                                      \
    const uint32_t y = add2(mul2(r.x, e[0]), e[2]), z = add2(mul2(r.y, e[1]), e[3]);                     \
    if (on) asm volatile("st.global.b32 [%0+%3], %1; st.global.b32 [%0+%4], %2;" ::"l"(out + eo), "r"(y), "r"(z), "n"(t * 16 * D_), "n"(t * 16 * D_ + 16) : "memory"); \
  }
#pragma unroll 1
      for (int s = s0; s < NSEG; s += 2) {
        float d[32];
        uint32_t e[4], f[4];
        uint4 r, q;
        float4 a, b;
        int prev = 0;
        const uint32_t par = (s >> 1) & 1;
        int u = s - 2 - 2 * pend;
#define eo (eb + u * 32 * D_)
#define xo (xb + (u & 31) * 256)
#pragma unroll
        for (int i = 0; i < 8; i++) {
          if (i == DQ) mbar_wait(dW, 1);
          mbar_wait(dFull + st * 8, ph);
          if (leader && (s | 2) == 50) TG(24 + wg * 8 + i, s & 2);
          const uint32_t db = dB + st * 1024;
          asm volatile("" : "+r"(dA));
          WG_FENCE();
#pragma unroll
          for (int k = 0; k < 8; k++) {
            const int h = d_head(i), bo = (k >> 2) * 512 + (k & 3) * 2;
            if (h < NRD) wgmma_rs64(d, W[h < NRD ? h * 8 + k : 0], DSC(db + bo), (i | k) != 0);
            else wgmma_ss64(d, DSC(dA + ((h - NRD) * 2 + (k >> 2)) * 1024 + (k & 3) * 128), DSC(db + bo));
            if (i == DPS && !(k & 1)) { if (k) SUM_ST(k / 2 - 1, pend, s - 2); SUM_LD(k / 2); }
            if (i == DP0) { if (k == 0) OPERANDS(0, e); if (k == 2) OPERANDS(1, f); if (k == DPK) RECV(); }
            if (i == 7) {
              if (k == 0) FIN_LD(fin);
              if (k == 2) { FIN_T(r, a); FIN_T(q, b); }
              if (k == 4) FIN_ST(0, e, r, fin);
              if (k == 5) FIN_ST(1, f, q, fin);
            }
          }
          WG_COMMIT();
          if (leader && (s | 2) == 50) TG(24 + wg * 8 + i, 1 + (s & 2));
          if (i == DPS) { SUM_ST(3, pend, s - 2); if (pend) XFREE(); }
          if (i > 0) { WG_WAIT(1); if (leader) mbar_arrive(dEmpty + prev * 8); }
          if (i == DPS - 1 && pend) mbar_wait(xF + wid * 8, par ^ 1);
          if (i == 6 && fin) CHECK();
          if (i == 2) asm volatile("prefetch.global.L2 [%0];" ::"l"(((lane & 1) ? x : g_gate) + eb + (s * 32 + (lane & 2) * 4) * D_));
          prev = st;
          if (++st == D_STAGES) { st = 0; ph ^= 1; }
        }
        fin = pend;
        asm volatile("{.reg .pred p, g; ld.volatile.shared.u32 %0, [%1]; setp.gt.s32 p, %0, %2; setp.eq.b32 g, %3, 0;\n"
                     "@g barrier.red.and.aligned.pred p, 1, 128, p; @!g barrier.red.and.aligned.pred p, 2, 128, p; selp.b32 %0, 1, 0, p;}"
                     : "=&r"(pend) : "r"(dReady), "r"(s + 3), "r"(wg) : "memory");
        mbar_wait(xE + wid * 8, par);
        WG_WAIT(0);
        asm volatile("" : D16(d));
        asm volatile("" : D16((d + 16)));
        if (leader) mbar_arrive(dEmpty + prev * 8);
#pragma unroll
        for (int j = 0; j < 8; j++) {
          const uint32_t a = in + (j >> 2) * 1024 + ((j) & 1) * 512;
          if ((((j) >> 1) & 1) == rank) sts_f4(a, d + 4 * j);
          else sta4(a + 2048 + peer, make_uint4(asu(d[4 * j]), asu(d[4 * j + 1]), asu(d[4 * j + 2]), asu(d[4 * j + 3])), xF + wid * 8 + peer);
        }
        if (tid == 0) TG(24 + s, 1);
        if (!pend) {
          u = s - 2 * fin;
          OPERANDS(0, e);
          OPERANDS(1, f);
          RECV();
          mbar_wait(xF + wid * 8, par);
#pragma unroll
          for (int j = 0; j < 4; j++) { SUM_LD(j); SUM_ST(j, 1, s); }
          if (s + 2 < NSEG) XFREE();
#pragma unroll 1
          while (u < s || s + 2 == NSEG) {
            CHECK();
            FIN_LD(true);
            FIN_T(r, a);
            FIN_T(q, b);
            FIN_ST(0, e, r, true);
            FIN_ST(1, f, q, true);
            if (u == s || s + 2 < NSEG) break;
            u = s;
            OPERANDS(0, e);
            OPERANDS(1, f);
            RECV();
          }
          fin = 1;
        }
      }
    }
    else PUBLISH();
    if (PP && !wg) bar_sync(4, 256);
#undef eo
#undef xo
    if (tid == 0) { TG(95, 3); ST(32 + cl); }
  }
  asm volatile("barrier.cluster.arrive.relaxed.aligned; barrier.cluster.wait.aligned;" ::: "memory");
}
struct RecMaps { CUtensorMap w[3], wb[3], wo, xn, xn1, xn2, ox; };
#define NR1 13
#define NLOW 5
constexpr int R_WS = 0, R_WO = 2 * (32 - NR1) * 2048, R_Q = R_WO + 81920, R_K = R_Q + 6144, R_G1 = R_K + 6144,
              R_XN = R_WO + 98304, R_MEM = R_XN + 16384, R_VX = R_MEM + 16384, R_VM = R_VX + 8192, R_O = R_VM + 4096,
              R_TS = R_O + 4096, R_SC = R_TS + 5120, R_BAR = R_SC + 1280, R_TAB = R_BAR + 256, R_SMEM = R_TAB + 128;
constexpr int STG = R_SC - 2 * (32 + NR1) * 2048, NDIR = STG / 2048;
__device__ constexpr int stg(int g, int i) { return STG + (i == 0 ? 131072 + g * NR1 * 2048 : (i == 1 ? g * 98304 : 32768 + g * 32768)); }
static_assert(R_SMEM <= 232448 && R_G1 + 2048 <= R_XN && STG % 1024 == 0 && R_WO <= STG + 32768 && R_XN >= STG + 98304, "smem");
constexpr uint32_t SB = 1024;
constexpr int POLL_LIM = 1 << 20;
enum { BAR_MEM = 1, BAR_RED, BAR_O, BAR_BG, BAR_C, BAR_G1, BAR_X, BAR_H, BAR_ST };
#define bC (sb + R_BAR)
#define bX (bC + 48)
#define bWS (bC + 128)
#define bWo (bC + 136)
#define bM (bC + 144)
#define bS (bC + 152)
#define bTs (bC + 176)
#define bIn (bC + 184)
#define bTok (bC + 192)
#define aInfo (bC + 200)
#define aCal (bC + 224)
constexpr int XC_G2N = 256, XC_PRB = 384, XC_T = 386;
#define TINIT 6200, 1050, 200, 300, 400
__constant__ int c_tune[16] = {TINIT};
#define T_STEP c_tune[0]
#define T_G2 c_tune[1]
#define D_G1 c_tune[2]
#define D_G2 c_tune[3]
#define T_REL c_tune[4]
#define NWF 2
#define NBF 2
#define NCH 1
#define PAT 1
#define INSM(k) ((k) % 5 % 2 == 0)
#define SIDX(k) ((k) / 5 * 3 + ((k) % 5 + 1) / 2)
#define RIDX(k) (INSM(k) ? 0 : (k) - SIDX(k))
#define NEA0 3
#define NEA1 3
#define NEB 2
#define HOLE0 6
#define HOLE1 6
#define GST 0
#define THR 0
#define LEAD 15
#define WOT 2
#define WOW 1
#define XPOS 0
#define NPRB 3
#define PFX 2

__device__ __forceinline__ void xn_pair(const CUtensorMap* m, uint32_t dst, uint32_t bar, int bytes, int n, int c, int half) {
  mbar_expect_tx(bar, bytes);
  asm volatile(
      "cp.async.bulk.tensor.4d.shared::cluster.global.mbarrier::complete_tx::bytes [%0], [%1, {%3, %4, %5, %6}], [%2];"
      ::"r"(dst), "l"(m), "r"(bar), "r"(0), "r"(n * 32), "r"(c), "r"(half) : "memory");
}

__global__ void __launch_bounds__(384, 1)
k_rec(const __grid_constant__ RecMaps maps, const bf16* __restrict__ x, const bf16* __restrict__ mem0, unsigned char* xch) {
  extern __shared__ __align__(1024) unsigned char smem_raw[];
  const uint32_t sb = smem_u32(smem_raw);
  if ((sb & 0xffffff) != SB) __trap();
  const int tid = threadIdx.x, wid = __shfl_sync(~0u, tid >> 5, 0), wg = wid >> 2, w = wid & 3;
  const int lane = tid & 31;
  const int cta = blockIdx.x, h = cta / 3, j = cta - h * 3, cl = h >> 1, r0 = (h & 1) * 3;
  const bool isA = j < 2;
  if (tid >= 32 && tid < 32 + 11) asm volatile("prefetch.tensormap [%0];" ::"l"(&maps.w[0] + (tid - 32)) : "memory");
  if (tid == 0 && cta == 0) ST(2);
  asm volatile("griddepcontrol.launch_dependents;" ::: "memory");
  uint32_t u[3][16] = {};
  const int row = min((cta * 8 + wid) * 3, S_ - 3);
  if (wg < 2) {
#pragma unroll
    for (int i = 0; i < 3; i++) row_ld(u[i], x + (size_t)(row + i) * D_, lane);
  }
  if (tid == 0) {
    for (int i = 0; i < 18; i++) mbar_init(bC + i * 8, 1);
    mbar_init(bM, 2); mbar_init(bS, 1); mbar_init(bTs, 1); mbar_init(bIn, 2); mbar_init(bTok, 4);
    asm volatile("fence.mbarrier_init.release.cluster;" ::: "memory");
  }
  if ((wid >> 1) != 4) {
    bar_sync(BAR_G1, 384);
#pragma unroll 1
    for (int pass = wg >> 1; pass < 2; pass++) {
      bf16* dst = (pass ? g_xn2 : g_xn) + (size_t)row * D_;
      if (pass == 0) {
        if (__any_sync(~0u, after(c_tune[15], u[0][15] ^ u[1][15] ^ u[2][15], c_tune[15]))) __trap();
        bar_arrive(BAR_X, 320);
        if (tid == 0) TG(1, 0);
      }
#pragma unroll
      for (int i = 0; i < 3; i++) ln_packed(u[i]);
      if (wg < 2 && (cta * 8 + wid) * 3 < S_) {
#pragma unroll
        for (int i = 0; i < 3; i++) row_st(u[i], dst + i * D_, lane);
      }
    }
  } else {
    bar_arrive(BAR_G1, 384);
    uint4* z = (uint4*)(xch + (isA ? (h * 2 + j) * 4 : XC_G2N + ((h >> 3) & 1) * 48 + (h >> 4) * 64 + ((h >> 1) & 3) * 4 + (h & 1)) * 4096);
#pragma unroll 4
    for (int i = 0; i < (isA ? 16 : 4); i++) z[i * 64 + (tid & 63)] = make_uint4(0, 0, 0, 0);
    if (cta == cl * 6) {
      uint32_t* p = (uint32_t*)(xch + (XC_PRB + w) * 4096 + cl * 128);
      st_rlx1(p + lane, 0);
      uint32_t lat = ~0u;
#pragma unroll 1
      for (int r = 0; r < NPRB && lane == 0; r++) {
        uint32_t v, c0 = clk32();
        asm volatile("atom.relaxed.gpu.global.add.u32 %0, [%1], 1;" : "=r"(v) : "l"(p) : "memory");
        if (v >> 30) break;
        lat = min(lat, clk32() - c0);
      }
      if (lane == 0) { sts_u1(aInfo + w * 4, lat); TG(3, w); }
      __syncwarp();
    }
  }
  asm volatile("barrier.cluster.arrive.relaxed.aligned;" ::: "memory");
#define WMAP(g) (&maps.w[isA ? (g) : 2])
#define WCOL(g) (h * 128 + (isA ? j : (g)) * 64)
  const uint32_t xlo = (uint32_t)(uint64_t)xch, xhi = (uint32_t)((uint64_t)xch >> 32);
#define XP(off) xptr(xlo + (off), xhi)
  if (wg < 2) {
    fence_async_all();
    if (tid == 0) TG(1, 1);
    if (wid != 7) bar_arrive(BAR_C, 256);
    else bar_sync(BAR_C, 256);
    if (tid == 224) { sig_cnt(C_LN); TG(0, 1); }
    __syncwarp();
    if (wid == 7) bar_arrive(BAR_BG, 96);
    asm volatile("setmaxnreg.inc.sync.aligned.u32 224;");
    const uint32_t l16c = opaque(sb + lane * 16);
    const uint32_t xwc = opaque(sb + ((lane >> 4) * 8 + (lane & 7)) * 128 + (((w * 2 + ((lane >> 3) & 1)) ^ (lane & 7)) << 4));
    uint32_t W0[32][4], W1[NR1][4];
#pragma unroll
    for (int i = 0; i < 3; i++) {
      mbar_wait(bC + (wg * 3 + i) * 8, 0);
      if (i == 0 && tid == 0) TG(1, 2);
#pragma unroll
      for (int k = 0; k < (i ? 16 : NR1); k++) ldsm4t(i ? W0[i ? i * 16 - 16 + k : 0] : W1[i ? 0 : k], (wg ? stg(1, i) : stg(0, i)) + k * 2048 + xwc);
      if (i) bar_arrive(i == 1 ? BAR_ST : BAR_H, 288);
    }
    if (tid == 0) TG(1, 3);
    asm volatile("barrier.cluster.wait.aligned;" ::: "memory");
    mbar_wait(bWS, 0);
    if (tid == 0) TG(0, 2);
    const uint32_t dX = (uint32_t)make_desc(SB + R_XN, 16, 1024, 1) + wg * 512, dW = (uint32_t)make_desc(SB + R_WS, 1024, 1024, 1) + wg * (32 - NR1) * 128;
    const uint32_t pB = peer_base(sb, r0 + 2);
#pragma unroll 1
    for (int s = 0; s < NSEG; s++) {
      uint32_t xw = xwc, l16 = l16c;
      asm volatile("" : "+r"(xw), "+r"(l16));
#define LANE0 ((l16 & 511) == 0)
      {
        float d0[16], d1[16];
#pragma unroll
        for (int c = 0; c < 8; c++) {
          if (c == 7 || !(c & 1)) mbar_wait(bX + (c < 4 ? c / 2 : (c == 7 ? 6 : c - 2) + wg) * 8, s & 1);
          if (c == NEB && s > 0 && !isA && wid == 7) {
            bar_sync(BAR_ST, 160);
            if (LANE0 && s > 1) sig_cnt(C_OX + s - 2, 4);
            __syncwarp();
          }
          if (c <= 3 && s > 0 && c == (isA ? (wg ? NEA1 : NEA0) : NEB)) bar_sync(BAR_BG, 384);
          if ((c == HOLE0 || c == HOLE1) && s > 0 && isA && c == (wg ? HOLE1 : HOLE0)) bar_sync(BAR_H, 384);
          const uint32_t db = dX + (c & 2) * 512 + (c & 1) * 256 + (c < 4 ? 0 : c_tune[15]);
          uint32_t tmp[4];
          if (c < NLOW) {
#pragma unroll
            for (int i = 0; i < 4; i++) asm volatile("or.b32 %0, %1, %2;" : "=r"(tmp[i]) : "r"(W0[c * 4][i]), "r"(c_tune[15]));
          }
          WG_FENCE();
#pragma unroll
          for (int kk = 0; kk < 4; kk++) {
            const int k = c * 4 + kk;
            if (c < 7) wgmma_rs32(d0, kk == 0 && c < NLOW ? tmp : W0[k], DSC(db + kk * 2), k != 0);
            if (kk == 0 && c + 1 < NLOW) WG_COMMIT();
            if (!INSM(k)) wgmma_rs32(d1, W1[RIDX(k)], DSC(db + kk * 2), k != 0);
            else wgmma_ss32(d1, DSC(dW + SIDX(k) * 128), DSC(db + kk * 2), k != 0);
          }
          WG_COMMIT();
          if (c == 7) {
#pragma unroll
            for (int kk = 0; kk < 4; kk++) wgmma_rs32(d0, W0[28 + kk], DSC(db + kk * 2), 1);
            WG_COMMIT();
          }
          const bool pause = c + 1 == (isA ? (wg ? NEA1 : NEA0) : NEB);
          if ((c == 1 || c == 2) && pause) WG_WAIT(0);
          if (c + 1 < NLOW || c == 4) WG_WAIT(1);
#pragma unroll
          for (int f = 1; f <= 3; f++) {
            if (f != c && f + 1 != c) continue;
            const bool early = f < 3 && f + 1 == (isA ? (wg ? NEA1 : NEA0) : NEB);
            if (w == 0 && LANE0 && early == (f == c)) {
              if (f == 1) {
                xn_pair(&maps.xn1, sb + R_XN + wg * 8192, bX + (2 + wg) * 8, 8192, s, 4, wg);
              } else {
                mbar_expect_tx(bX + (f * 2 + wg) * 8, 4096);
                tma_load_2d(sb + R_MEM + wg * 8192 + (f - 2) * 4096, &maps.xn, wg * 512 + (f + 4) * 64, s * 32, bX + (f * 2 + wg) * 8);
              }
            }
            __syncwarp();
          }
        }
        const uint32_t ex = l16 + R_XN + w * 2048;
        WG_WAIT(1);
        asm volatile("" : D16(d1));
#pragma unroll
        for (int i = 0; i < 4; i++) sts_f4(ex + wg * 8192 + i * 512, d1 + 4 * i);
        bar_sync(BAR_C, 256);
#pragma unroll
        for (int i = 0; i < 4; i++) {
          const float4 x = lds_f4(ex + (wg ^ 1) * 8192 + i * 512);
          d1[4 * i] = x.x; d1[4 * i + 1] = x.y; d1[4 * i + 2] = x.z; d1[4 * i + 3] = x.w;
        }
        WG_WAIT(0);
        asm volatile("" : D16(d0));
        if (w == 0 && LANE0) mbar_arrive(bM);
        if (s > 0 && tid < 32) { s--; TR(17); s++; }
        uint32_t f[8];
#pragma unroll
        for (int i = 0; i < 8; i++) f[i] = pack_bf16(d0[2 * i] + d1[2 * i], d0[2 * i + 1] + d1[2 * i + 1]);
        if (isA) {
          const uint32_t aq = l16 + (l16 & 256) * 3 + R_Q + wg * 6144 + w * 256;
          stsm4t(aq, f[0], f[1], f[2], f[3]);
          stsm4t(aq + 2048, f[4], f[5], f[6], f[7]);
        } else {
          const uint32_t av = l16 + R_VX + w * 2048 + wg * 1024;
          if (s > 0) mbar_wait(bTok, (s - 1) & 1);
          sts_u4(av, make_uint4(f[0], f[1], f[2], f[3])); sts_u4(av + 512, make_uint4(f[4], f[5], f[6], f[7]));
        }
        if (s > 0 && tid < 32) { s--; TR(18); s++; }
      }
      {
        const uint32_t aW = xw + R_WS + wg * (32 - NR1) * 2048, aMem = l16 + R_MEM + wg * 8192;
        float a[4][4];
        uint32_t b[16][4], f[32 - NR1][4], ck[14];
#define PAIR(i) (i)
#pragma unroll
        for (int i = 0; i < NWF; i++) ldsm4t(f[i], aW + i * 2048);
#pragma unroll
        for (int i = 0; i < 4; i++) a[i][0] = a[i][1] = a[i][2] = a[i][3] = 0.f;
        bar_sync(BAR_MEM, 384);
#pragma unroll
        for (int i = 0; i < NBF - 1; i++) ldsm4t(b[i], aMem + PAIR(i) * 512);
#pragma unroll
        for (int i = 0; i < 16; i++) {
          const int p = PAIR(i);
          if (i + NBF - 1 < 16) ldsm4t(b[i + NBF - 1], aMem + PAIR(i + NBF - 1) * 512);
#pragma unroll
          for (int e = 0; e < 2; e++) {
            const int k = 2 * PAIR(i > 0 ? i - 1 : 0) + e, q = SIDX(k) + NWF;
            if (i > 0 && INSM(k) && q < 32 - NR1) ldsm4t(f[q], aW + q * 2048);
          }
          if (i < 14) ck[i] = clk32();
          if (i == 1 && tid < 32) TRX(0, ck[0]);
          if (i > 1) ck[0] |= ck[i - 2];
#pragma unroll
          for (int e = 0; e < 2; e++) {
            const int k = 2 * p + e;
            const uint32_t* u = INSM(k) ? f[INSM(k) ? SIDX(k) : 0] : W1[RIDX(k)];
            mma16816(a[2 + e % NCH], u[0], u[1], u[2], u[3], b[i][2 * e], b[i][2 * e + 1]);
            mma16816(a[e % NCH], W0[k][0], W0[k][1], W0[k][2], W0[k][3], b[i][2 * e], b[i][2 * e + 1]);
          }
        }
        l16 = after(l16, ck[0], 0);
        if (NCH == 2) {
#pragma unroll
          for (int i = 0; i < 4; i++) { a[0][i] += a[1][i]; a[2][i] += a[3][i]; }
        }
        const uint4 r = make_uint4(pack_bf16(a[0][0], a[0][1]), pack_bf16(a[0][2], a[0][3]), pack_bf16(a[2][0], a[2][1]), pack_bf16(a[2][2], a[2][3]));
        if (!isA) {
          sts_u4(l16 + R_VM + wid * 512, r);
          bar_arrive(BAR_RED, 384);
          if (tid < 32) TR(1);
          if (tid == 160) TRCAL(s);
          __syncwarp();
          continue;
        }
        stsm4t((l16 & ~256u) + (((l16 >> 8) & 1) ^ wg) * 6144 + R_Q + 4096 + wg * 1024 + w * 256, r.x, r.y, r.z, r.w);
        bar_arrive(BAR_RED, 384);
        fence_async_smem();
        bar_sync(BAR_X, 352);
        if (tid < 32) TR(1);
        if (tid == 160) TRCAL(s);
        __syncwarp();
      }
      if (wg == 0) {
        float c[24];
        WG_FENCE();
#pragma unroll
        for (int i = 0; i < 4; i++) wgmma_ss48(c, make_desc(SB + R_Q + i * 256, 128, 1024, 0), make_desc(SB + R_K + i * 256, 128, 1024, 0), i != 0);
        WG_COMMIT();
        asm volatile("" : "+r"(l16));
        const uint32_t at = l16 + R_TS + w * 2560 + j * 640 + pB, au = at + 512 - (l16 & 511) / 4 * 3;
        mbar_wait(bIn, s & 1);
        WG_WAIT(0);
        asm volatile("" : D16(c), "+f"(c[16]), "+f"(c[17]), "+f"(c[18]), "+f"(c[19]), "+f"(c[20]), "+f"(c[21]), "+f"(c[22]), "+f"(c[23]));
        if (w < 2) {
#pragma unroll
          for (int r = 0; r < 2; r++) {
            const float* e = c + 2 * r;
            sta4(at + r * 1280, make_uint4(pack_bf16(e[0], e[1]), pack_bf16(e[4], e[5]), pack_bf16(e[8], e[9]), pack_bf16(e[12], e[13])), bTs + pB);
            sta1(au + r * 1280, pack_bf16(e[16] + e[20], e[17] + e[21]), bTs + pB);
          }
        }
        if (tid < 32) TR(14);
      }
    }
  } else {
    asm volatile("setmaxnreg.dec.sync.aligned.u32 56;");
    const int at = tid & 127, red = h * 2 + j;
    const int g = w & 1, slot = g * (32 - NR1) + SIDX(lane);
    if (w >= 2) {
      const bool lead = cl == LEAD;
      if (lead) bar_arrive(BAR_X, 320);
      else bar_sync(BAR_X, 320);
      if (lane < 3) mbar_expect_tx(bC + (g * 3 + lane) * 8, lane ? 32768 : NR1 * 2048);
      if (lane == 3 && g) mbar_expect_tx(bWS, R_WO);
      if (!INSM(lane)) tma_load_2d_ef(sb + stg(0, 0) + (g * NR1 + RIDX(lane)) * 2048, WMAP(g ^ 1), WCOL(g ^ 1), g * 512 + lane * 16, bC + g * 24);
      __syncwarp();
#pragma unroll 1
      for (int i = 0; i < 3; i++) {
        if (i == (lead ? 2 : XPOS)) bar_sync(BAR_BG, 96);
        if (i >= THR && !lead) mbar_wait(bC + (g * 3 + i - THR) * 8, 0);
        if (lane == 0 && i < 2) tma_load_2d_ef(sb + STG + (i ? g + 1 : g * 3) * 32768, WMAP(g) + 3, WCOL(g), g * 512 + i * 256, bC + (g * 3 + 1 + i) * 8);
        __syncwarp();
      }
      if (INSM(lane) && slot < NDIR) tma_load_2d_ef(sb + R_WS + slot * 2048, WMAP(g ^ 1), WCOL(g ^ 1), g * 512 + lane * 16, bWS);
      __syncwarp();
    }
    if (w == 3) {
      bar_sync(BAR_ST, 288);
      fence_async_smem();
      if (INSM(lane) && slot >= NDIR) tma_load_2d_ef(sb + R_WS + slot * 2048, WMAP(0), WCOL(0), 512 + lane * 16, bWS);
      __syncwarp();
      if (lane < 2) {
        wait_cnt(C_LN, gridDim.x);
        fence_async_all();
        xn_pair(&maps.xn2, sb + R_XN + lane * 16384, bX + lane * 8, 16384, 0, lane * 2, 0);
        TG(2, 1);
      }
      __syncwarp();
    }
    if (w < 2) bar_sync(BAR_RED, 64);
    if (at == 0) {
      uint32_t v = 1;
      if (cta == cl * 6) v += ((__popc((XC_PRB + (lds_u1(aInfo + 4) < lds_u1(aInfo))) & 0xb3) & 1) << cl) << 16;
      asm volatile("red.release.gpu.global.add.u32 [%0], %1;" ::"l"(g_cnt + C_CHK * 8), "r"(v) : "memory");
      int n = 0;
#pragma unroll 1
      do {
        asm volatile("ld.acquire.gpu.global.u32 %0, [%1];" : "=r"(v) : "l"(g_cnt + C_CHK * 8) : "memory");
      } while ((v & 0xffff) < gridDim.x && ++n < WAIT_LIM);
      sts_u1(aInfo + 8, v >> 16);
      TG(2, 0);
    }
    bar_sync(BAR_O, 128);
    const uint32_t pmask = __shfl_sync(~0u, lds_u1(aInfo + 8), 0), myp = (pmask >> cl) & 1;
    const int nt = isA ? 5 : 6;
    uint32_t mytile = 0;
    {
      int n = 0;
      for (int far = 1; far >= 0; far--)
        for (int i = 0; i < nt; i++) {
          const int T = j * 5 + i, p = (pmask >> T) & 1;
          if ((p ^ myp) != far) continue;
          if (n == lane) {
            mytile = T;
            sts_u1(sb + R_TAB + w * 32 + n * 4, xlo + xchunk((T * 4 + w) * 4 + (h >> 4) * 2, p) + (h & 15) * 256);
          }
          n++;
        }
    }
    if (w == 3) {
      bar_sync(BAR_H, 288);
      fence_async_smem();
      if (WOW) mbar_wait(bWS, 0);
#pragma unroll 1
      for (int i = 0; i < nt; i++) {
        if (i >= WOT) mbar_wait(bC + (i - WOT) * 8, 1);
        const bool tail = i >= nt - WOT;
        if (lane == i) {
          if (!tail || i == nt - 1) mbar_expect_tx(tail ? bWo : bC + i * 8, tail ? WOT * 16384 : 16384);
          tma_load_2d(sb + R_WO + i * 16384, &maps.wo, mytile * 64, h * 128, tail ? bWo : bC + i * 8);
        }
        __syncwarp();
      }
    }
    asm volatile("barrier.cluster.wait.aligned;" ::: "memory");
    {
      uint4 v[8];
#pragma unroll
      for (int i = 0; i < 8; i++) v[i] = __ldg((const uint4*)(mem0 + (lane >> 2) * D_ + w * 256 + i * 32 + (lane & 3) * 8));
      mbar_wait(bM, 0);
#pragma unroll
      for (int i = 0; i < 8; i++)
        stsm4t(sb + R_MEM + w * 4096 + i * 512 + (lane & 6) * 64 + (lane >> 3) * 32 + (lane & 1) * 16, v[i].x, v[i].y, v[i].z, v[i].w);
    }
    if (at == 96) { const uint2 e = timer_edge(); sts_u2(aCal, e.x, e.y); }
    int lim = POLL_LIM;
    const uint32_t l8c = opaque(lane * 8);
    const uint32_t pA = peer_base(sb, r0), pB = peer_base(sb, r0 + 2 - (j >> 1));
    const uint32_t uR = xchunk(red * 4 + (w & 2), myp) + (w & 1) * 2048;
    const uint32_t uW = xchunk(XC_G2N + (red >> 4) * 4, (myp ^ w ^ 1) & 1) + (red & 15) * 256;
    const uint32_t uG = xchunk(XC_G2N, myp) + w * 512;
    const uint64_t dWo = make_desc(SB + R_WO, 1024, 1024, 1), dO = make_desc(SB + R_O, 128, 128, 0);
#pragma unroll 1
    for (int s = 0; s < NSEG; s++) {
      const uint32_t tag = (s & 1) ^ 1, par = s & 1;
      const bool more = s + 1 < NSEG;
      uint32_t l8 = l8c;
      asm volatile("" : "+r"(l8));
#define STORE_OX(n, w) do {                                                                 \
          tma_store_2d(&maps.ox, sb + R_O + (w) * 1024, h * 128 + (w) * 16, (n) * 32);         \
          tma_store_2d(&maps.ox, sb + R_TS + (w) * 1280, h * 128 + 64 + (w) * 16, (n) * 32); } while (0)
      bar_sync(BAR_MEM, 384);
      if (w == 3) {
        if (l8 == 0) {
          const uint32_t ta = ld_rlx1(XP(XC_T << 12));
          if (more) {
            fence_async_smem();
            xn_pair(&maps.xn2, sb + R_XN, bX, 16384, s + 1, 0, 0);
            mbar_expect_tx(bS, isA ? 2048 : 1280);
          }
          if (!isA) mbar_expect_tx(bTs, 5120);
          const uint4 o = lds_u4(aCal);
          const uint2 e = timer_edge();
          float f = (float)(e.y - o.y) * rcp((float)(e.x - o.x));
          if (s > 1) f = 0.75f * asf(o.z) + 0.25f * f;
          uint32_t d = (int)((float)(int)(ta - e.x) * f);
          if (d > 8192) d = 0;
          sts_u4(aCal, make_uint4(e.x, e.y, asu(f), ta));
#pragma unroll
          for (int i = 0; i < 4; i++) sts_u1(sb + R_TAB + i * 32 + 24, e.y + d);
        }
        if (s + PFX < NSEG && l8 < 128)
          asm volatile("prefetch.global.L2 [%0];" ::"l"(g_xn + (size_t)(s + PFX) * 32 * D_ + (cta & 31) * 1024 + l8 * 8));
      }
#define XN23() do { if (w == 3 && l8 == 0 && more) { fence_async_smem(); xn_pair(&maps.xn2, sb + R_MEM, bX + 8, 16384, s + 1, 2, 0); } __syncwarp(); } while (0)
      if (s == 0 && at == 0) TG(2, 3);
      if (s == 0) mbar_wait(bWo, 0);
      if (s == 0 && at == 0) TG(2, 2);
      if (isA && more && w < 3) {
        uint32_t k[4][4], q[4][4];
        uint32_t ak = sb + R_K + w * 2048 + l8 * 2 + (l8 & 128) * 6, aq = sb + R_Q + 4096 + (l8 & 63) * 2 + (l8 & 64) * 16 + (l8 & 128);
        asm volatile("" : "+r"(ak), "+r"(aq));
        if (w == 2) bar_sync(BAR_RED, 384);
#pragma unroll
        for (int i = 0; i < 4; i++) ldsm4(k[i], ak + i * 256);
        if (w != 2) bar_sync(BAR_RED, 384);
#pragma unroll
        for (int i = 0; i < 4; i++) ldsm4(q[i], aq + i * 256);
        float c[4][4];
#pragma unroll
        for (int i = 0; i < 4; i++) c[i][0] = c[i][1] = c[i][2] = c[i][3] = 0.f;
#pragma unroll
        for (int i = 0; i < 4; i++) {
          mma16816(c[i & 1], q[i][0], q[i][1], q[i][2], q[i][3], k[i][0], k[i][1]);
          mma16816(c[2 + (i & 1)], q[i][0], q[i][1], q[i][2], q[i][3], k[i][2], k[i][3]);
        }
        const float a0 = (c[0][0] + c[0][2]) + (c[1][0] + c[1][2]), a1 = (c[0][1] + c[0][3]) + (c[1][1] + c[1][3]);
        const float b0 = (c[2][0] + c[2][2]) + (c[3][0] + c[3][2]), b1 = (c[2][1] + c[2][3]) + (c[3][1] + c[3][3]);
        const uint32_t as = sb + R_SC + j * 640 + w * 256;
        if (w < 2) {
          const uint32_t x = pack_bf16(a0, a1), y = pack_bf16(b0, b1);
          sta2(as + l8 + pB, x, y, bS + pB);
        } else {
          const uint32_t x = pack_bf16(a0 + b0, a1 + b1);
          sta1(as + (l8 >> 1) + pB, x, bS + pB);
        }
        bar_arrive(BAR_X, 352);
        if (w == 0) TR(2);
      } else if (isA) {
        bar_sync(BAR_RED, 384);
        if (w < 3) bar_arrive(BAR_X, 352);
        XN23();
      } else {
        if (w < 2 && l8 == 0) {
          if (s > 0) {
            fence_async_smem();
            STORE_OX(s - 1, 2 * w); STORE_OX(s - 1, 2 * w + 1);
            asm volatile("cp.async.bulk.commit_group; cp.async.bulk.wait_group.read 0;" ::: "memory");
          }
          arrive_remote(bIn + pA); arrive_remote(bIn + pB);
          if (!more) { asm volatile("cp.async.bulk.wait_group 0;" ::: "memory"); sig_cnt(C_OX + s - 1, 2); }
        }
        __syncwarp();
        uint4 vx[4];
#pragma unroll
        for (int i = 0; i < 4; i++) vx[i] = lds_u4(sb + R_VX + (i & 1) * 1024 + (i >> 1) * 512 + w * 2048 + l8 * 2);
        bar_sync(BAR_RED, 384);
        XN23();
        if (more) {
          const uint32_t am = sb + R_VM + w * 512 + l8 * 2;
          const uint2 vm[4] = {lds_u2(am), lds_u2(am + 2056), lds_u2(am + 8), lds_u2(am + 2048)};
          mbar_wait(bS, par);
          if (w == 0) TR(4);
          float sc[10];
          const uint2 u0 = lds_u2(sb + R_SC + l8), u1 = lds_u2(sb + R_SC + 256 + l8), v0 = lds_u2(sb + R_SC + 640 + l8), v1 = lds_u2(sb + R_SC + 896 + l8);
          sum_scores(sc, u0, u1, lds_u1(sb + R_SC + 512 + (l8 >> 1)), v0, v1, lds_u1(sb + R_SC + 1152 + (l8 >> 1)));
          uint32_t p[5];
          softmax_e(sc);
#pragma unroll
          for (int i = 0; i < 5; i++) p[i] = pack_bf16(sc[2 * i], sc[2 * i + 1]);
          if (w == 0) TR(5);
          float o0[4], o1[4], sm[4];
          pv_mma(o0, o1, sm, vx, vm, p);
          const float i0 = rcp(sm[0]), i1 = rcp(sm[1]);
          const uint32_t aO = sb + R_O + w * 512 + (l8 >> 1);
          const uint32_t o[4] = {pack_bf16(o0[0] * i0, o0[1] * i1), pack_bf16(o0[2] * i0, o0[3] * i1), pack_bf16(o1[0] * i0, o1[1] * i1), pack_bf16(o1[2] * i0, o1[3] * i1)};
#pragma unroll
          for (int i = 0; i < 4; i++) { sta1(aO + i * 128 + pA, o[i], bS + pA); sta1(aO + i * 128 + pB, o[i], bS + pB); }
#pragma unroll
          for (int i = 0; i < 4; i++) sts_u1(aO + i * 128, o[i]);
          asm volatile("cp.async.bulk.wait_group 0;" ::: "memory");
        }
      }
      if (!more && isA) break;
      const uint32_t ts = sb + R_TS + w * 1280;
      uint4 tu, tv;
      uint32_t tu4, tv4, tp = 0;
#define LOAD_TS() tu = lds_u4(ts + l8 * 2); tv = lds_u4(ts + 640 + l8 * 2); tu4 = lds_u1(ts + 512 + (l8 >> 1)); tv4 = lds_u1(ts + 1152 + (l8 >> 1))
      if (!more) {
        mbar_wait(bTs, par);
        LOAD_TS();
      } else {
        float m[6][4];
        const uint4 ta = lds_u4(sb + R_TAB + w * 32);
        const uint4 tb = lds_u4(sb + R_TAB + w * 32 + 16);
        tp = tb.z;
        if (isA) mbar_wait(bS, par);
        else bar_sync(BAR_ST, 160);
        fence_async_smem();
        if (w == 0) TR(8);
        WG_FENCE();
#define WO_GROUP(t0, t1)                                                                                          \
  _Pragma("unroll") for (int kk = 0; kk < 8; kk++) _Pragma("unroll") for (int i = t0; i < t1; i++)                \
      wgmma_n8_tt(m[i], dWo + i * 1024 + kk * 128, dO + (kk & 3) * 32 + (kk >> 2) * 16, kk != 0);                 \
  WG_COMMIT();
        WO_GROUP(0, 3)
        if (isA) { wgmma_n8_tt(m[5], dWo, dO, 0); WO_GROUP(3, 5) } else { WO_GROUP(3, 6) }
#define G1_SEND(i, lo) st_rlx2(xptr(lo + l8, xhi), tagu(pack_bf16(m[i][0], m[i][1]), tag), pack_bf16(m[i][2], m[i][3]))
#define PIN4(i) asm volatile("" : "+f"(m[i][0]), "+f"(m[i][1]), "+f"(m[i][2]), "+f"(m[i][3]))
        WG_WAIT(1);
        PIN4(0); PIN4(1); PIN4(2);
        G1_SEND(0, ta.x); G1_SEND(1, ta.y); G1_SEND(2, ta.z);
        mbar_wait(isA ? bS : bTs, par);
        LOAD_TS();
        WG_WAIT(0);
        PIN4(3); PIN4(4); PIN4(5);
        bar_arrive(BAR_BG, 384);
        G1_SEND(3, ta.w); G1_SEND(4, tb.x);
        if (!isA) G1_SEND(5, tb.y);
        if (w == 0) TR(9);
      }
      const uint32_t slot = ((s & 1) * 48 + (s & 2) * 32) << 12;
      asm volatile("" : "+r"(l8));
      if (isA) {
        const unsigned char* pR = XP(uR + l8);
        unsigned char* pW = XP(((uW + slot) ^ ((w & 2) << 17)) + l8);
        uint32_t sel = (l8 >> 6) == ((l8 >> 3) & 3) ? (l8 & 32 ? 0x3F800000u : 0x3F80u) : 0;
        asm volatile("" : "+r"(sel), "+l"(pR), "+l"(pW));
        uint32_t ci = wait_clk(tp, D_G1), bad;
        if (w == 0) TRX(10, ci);
#pragma unroll 1
        do {
          uint2 p[8];
#pragma unroll
          for (int i = 0; i < 8; i++) p[i] = ld_rlx2(pR + i * 256);
          ci = clk32();
          float d[2][4] = {};
#pragma unroll
          for (int i = 0; i < 4; i++) mma16816(d[i & 1], p[2 * i].x, p[2 * i].y, p[2 * i + 1].x, p[2 * i + 1].y, sel, sel);
          bad = or3(ne2(p[0].x, p[1].x, tag), ne2(p[2].x, p[3].x, tag), ne2(p[4].x, p[5].x, tag)) | ne2(p[6].x, p[7].x, tag);
          sts_u2(sb + R_G1 + w * 512 + l8, asu(d[0][0] + d[1][0]), asu(d[0][1] + d[1][1]));
          sts_u2(sb + R_G1 + w * 512 + 256 + l8, asu(d[0][2] + d[1][2]), asu(d[0][3] + d[1][3]));
        } while (__any_sync(~0u, (bad & 1) && --lim > 0));
        bar_sync(BAR_G1, 128);
        if (w < 2) {
          const float4 a = lds_f4(sb + R_G1 + l8 * 2), b = lds_f4(sb + R_G1 + 512 + l8 * 2), c = lds_f4(sb + R_G1 + 1024 + l8 * 2), d = lds_f4(sb + R_G1 + 1536 + l8 * 2);
          st_rlx2(pW, nz(pack_bf16((a.x + b.x) + (c.x + d.x), (a.y + b.y) + (c.y + d.y))),
                  nz(pack_bf16((a.z + b.z) + (c.z + d.z), (a.w + b.w) + (c.w + d.w))));
        } else {
          st_rlx2(pW, 0, 0);
        }
        bar_arrive(BAR_H, 384);
        if (w == 0) TR(12);
        if (w == 0) TRX(11, ci);
        if (cta == 0 && w == 3) {
          const uint4 o = lds_u4(aCal);
          const bool late = (int)(ci - tp) > 200;
          st_rlx1(XP(XC_T << 12), (late ? o.x : o.w) + (int)((float)(int)(T_STEP + (late ? ci - o.y + T_REL : 0)) * rcp(asf(o.z))));
        }
      } else {
        const uint32_t av = sb + R_VX + w * 2048 + l8 * 2, am = sb + R_VM + w * 512 + l8 * 2;
        float sc[10];
        sum_scores(sc, make_uint2(tu.x, tu.y), make_uint2(tu.z, tu.w), tu4, make_uint2(tv.x, tv.y), make_uint2(tv.z, tv.w), tv4);
        uint4 x = lds_u4(av), y = lds_u4(av + 512);
        uint2 m0 = lds_u2(am), m1 = lds_u2(am + 2056);
        const int lim_k = w * 8 + (l8 >> 5) - ((l8 >> 2) & 6);
#pragma unroll
        for (int i = 0; i < 8; i++)
          if ((i >> 1) * 8 + (i & 1) > lim_k) sc[i] = -1.0e9f * 11.313708498984761f;
        softmax_e(sc);
        float sum = ((sc[0] + sc[1]) + (sc[2] + sc[3])) + ((sc[4] + sc[5]) + (sc[6] + sc[7])) + (sc[8] + sc[9]);
        sum += __shfl_xor_sync(~0u, sum, 1);
        sum += __shfl_xor_sync(~0u, sum, 2);
        const float inv = rcp(sum);
#pragma unroll
        for (int i = 0; i < 6; i++) sts_u1(ts + i * 128 + (l8 >> 1), pack_bf16(sc[i < 5 ? 2 * i : 8] * inv, sc[i < 5 ? 2 * i + 1 : 9] * inv));
        fence_async_smem();
        bar_sync(BAR_O, 128);
        const uint32_t ao = sb + (l8 & 128) * 2 + (l8 & 56) * 4 + (((l8 >> 2) ^ (l8 >> 1)) & 16);
#pragma unroll
        for (int t = 0; t < 2; t++) {
          const uint32_t a0[4] = {x.x, x.y, x.z, x.w}, a1[4] = {y.x, y.y, y.z, y.w}, a2[4] = {m0.x, m0.y, m1.x, m1.y};
          float d[16];
          WG_FENCE();
          wgmma_rs32(d, a0, make_desc(SB + R_TS, 128, 1280, 0), 0);
          wgmma_rs32(d, a1, make_desc(SB + R_TS + 256, 128, 1280, 0), 1);
          wgmma_rs32(d, a2, make_desc(SB + R_TS + 512, 128, 1280, 0), 1);
          WG_COMMIT();
          if (t == 0) { x = lds_u4(av + 1024); y = lds_u4(av + 1536); m0 = lds_u2(am + 8); m1 = lds_u2(am + 2048); }
          WG_WAIT(0);
          asm volatile("" : D16(d));
          if (t == 0) {
#define CPY(v) asm volatile("or.b32 %0, %0, %1;" : "+r"(v) : "r"(c_tune[15]))
            CPY(x.x); CPY(x.y); CPY(x.z); CPY(x.w); CPY(y.x); CPY(y.y); CPY(y.z); CPY(y.w); CPY(m0.x); CPY(m0.y); CPY(m1.x); CPY(m1.y);
            __syncwarp();
            if (l8 == 0) mbar_arrive(bTok);
          }
          stsm4t(ao + (t ? R_TS + w * 1280 : R_O + w * 1024), pack_bf16(d[0], d[1]), pack_bf16(d[2], d[3]), pack_bf16(d[4], d[5]), pack_bf16(d[6], d[7]));
          stsm4t(ao + (t ? R_TS + w * 1280 : R_O + w * 1024) + 512, pack_bf16(d[8], d[9]), pack_bf16(d[10], d[11]), pack_bf16(d[12], d[13]), pack_bf16(d[14], d[15]));
        }
        if (w == 0) TR(13);
        if (!more) {
          fence_async_smem();
          __syncwarp();
          if (l8 == 0) {
            STORE_OX(s, w);
            asm volatile("cp.async.bulk.commit_group; cp.async.bulk.wait_group 0;" ::: "memory");
            sig_cnt(C_OX + s);
            if (w == 0) TG(0, 3);
            if (cta == 2) ST(4);
          }
          break;
        }
      }
      {
        const unsigned char* src = XP(uG + slot + l8 * 2);
        const uint32_t dst = sb + R_MEM + w * 512 + l8 * 2;
        wait_clk(tp + T_G2, isA ? D_G2 : 0);
        if (w == 0) TR(16);
        uint4 p[8];
#pragma unroll
        for (int i = 0; i < 8; i++) p[i] = ld_rlx4(src + (i >> 1) * 16384 + (i & 1) * 2048);
        mbar_wait(bM, par ^ 1);
        uint32_t mn = ~0u, ck = 0;
#pragma unroll
        for (int i = 0; i < 8; i += 2) {
          mn = __vimin3_u32(mn, p[i].x, p[i + 1].x);
          asm volatile("" : "+r"(mn));
          sts_u4(dst + i * 2048, p[i]);
          sts_u4(dst + i * 2048 + 2048, p[i + 1]);
          mn = __vimin3_u32(mn, __vimin3_u32(p[i].y, p[i].z, p[i].w), __vimin3_u32(p[i + 1].y, p[i + 1].z, p[i + 1].w));
          asm volatile("" : "+r"(mn));
        }
        if (__builtin_expect(__any_sync(~0u, mn == 0u), 0)) {
#pragma unroll 1
          do {
#pragma unroll
            for (int i = 0; i < 8; i++) reld4(p[i], src + (i >> 1) * 16384 + (i & 1) * 2048, min4(p[i]));
            mn = ~0u;
#pragma unroll
            for (int i = 0; i < 8; i++) { sts_u4(dst + i * 2048, p[i]); mn = min(mn, min4(p[i])); }
          } while (__any_sync(~0u, mn == 0u && --lim > 0));
          lim = after(lim, ck, 0);
        }
        if (w == 0) TR(15);
      }
    }
  }
  asm volatile("barrier.cluster.arrive.relaxed.aligned; barrier.cluster.wait.aligned;" ::: "memory");
}

typedef CUresult (*EncodeFn)(CUtensorMap*, CUtensorMapDataType, cuuint32_t, void*, const cuuint64_t*, const cuuint64_t*,
                             const cuuint32_t*, const cuuint32_t*, CUtensorMapInterleave, CUtensorMapSwizzle,
                             CUtensorMapL2promotion, CUtensorMapFloatOOBfill);
static EncodeFn g_encode = nullptr;

#define PROMO CU_TENSOR_MAP_L2_PROMOTION_L2_256B
static void map2d(CUtensorMap* m, const void* p, uint64_t cols, uint64_t rows, uint32_t bc, uint32_t br,
                  CUtensorMapSwizzle sw) {
  cuuint64_t dims[2] = {cols, rows}, strides[1] = {cols * 2};
  cuuint32_t box[2] = {bc, br}, es[2] = {1, 1};
  g_encode(m, CU_TENSOR_MAP_DATA_TYPE_BFLOAT16, 2, (void*)p, dims, strides, box, es, CU_TENSOR_MAP_INTERLEAVE_NONE, sw,
           sw == CU_TENSOR_MAP_SWIZZLE_64B ? PROMO : CU_TENSOR_MAP_L2_PROMOTION_L2_256B, CU_TENSOR_MAP_FLOAT_OOB_FILL_NONE);
}
static void map_w(CUtensorMap* m, const void* p, uint64_t N, uint64_t K) {
  cuuint64_t dims[3] = {64, K, N / 64}, strides[2] = {N * 2, 128};
  cuuint32_t box[3] = {64, 64, 2}, es[3] = {1, 1, 1};
  g_encode(m, CU_TENSOR_MAP_DATA_TYPE_BFLOAT16, 3, (void*)p, dims, strides, box, es, CU_TENSOR_MAP_INTERLEAVE_NONE,
           CU_TENSOR_MAP_SWIZZLE_128B, CU_TENSOR_MAP_L2_PROMOTION_L2_256B, CU_TENSOR_MAP_FLOAT_OOB_FILL_NONE);
}
static void map_seg(CUtensorMap* m, const void* p, uint64_t K, uint64_t parts, uint32_t np, CUtensorMapL2promotion pr = CU_TENSOR_MAP_L2_PROMOTION_L2_256B) {
  cuuint64_t dims[4] = {64, S_, K / 64 / parts, parts}, strides[3] = {K * 2, 128, K * 2 / parts};
  cuuint32_t box[4] = {64, 32, 2, np}, es[4] = {1, 1, 1, 1};
  g_encode(m, CU_TENSOR_MAP_DATA_TYPE_BFLOAT16, 4, (void*)p, dims, strides, box, es, CU_TENSOR_MAP_INTERLEAVE_NONE,
           CU_TENSOR_MAP_SWIZZLE_128B, pr, CU_TENSOR_MAP_FLOAT_OOB_FILL_NONE);
}
template <typename T>
static void* sym(T& s) { void* p = nullptr; cudaGetSymbolAddress(&p, s); return p; }

static void map_a(CUtensorMap* m, const void* p, int K) { map2d(m, p, K, S_, 64, 128, CU_TENSOR_MAP_SWIZZLE_128B); }
static void map_c(CUtensorMap* m, const void* p, int N) { map2d(m, p, N, S_, 64, 16, CU_TENSOR_MAP_SWIZZLE_128B); }

extern "C" void kernel_launch(void* const* d_in, const int* in_sizes, int n_in, void* d_out, int out_size) {
  const bf16* x = (const bf16*)d_in[0];
  const bf16* mem0 = (const bf16*)d_in[1];
  const bf16* Wo = (const bf16*)d_in[5];
  const bf16* w1 = (const bf16*)d_in[8];
  const bf16* w2 = (const bf16*)d_in[9];
  const bf16* w3 = (const bf16*)d_in[10];
  const bf16* w4 = (const bf16*)d_in[11];
  if (!g_encode) {
    void* fn = nullptr;
    cudaDriverEntryPointQueryResult qr;
    cudaGetDriverEntryPoint("cuTensorMapEncodeTiled", &fn, cudaEnableDefault, &qr);
    g_encode = (EncodeFn)fn;
    cudaFuncSetAttribute(k_gemm, cudaFuncAttributeMaxDynamicSharedMemorySize, G_SMEM);
    cudaFuncSetAttribute(k_rec, cudaFuncAttributeMaxDynamicSharedMemorySize, R_SMEM);
  }
  const bf16 *xn = (bf16*)sym(g_xn), *xn2 = (bf16*)sym(g_xn2), *gate = (bf16*)sym(g_gate), *ox = (bf16*)sym(g_ox),
             *h1 = (bf16*)sym(g_h1), *x1 = (bf16*)sym(g_x1), *ln1 = (bf16*)sym(g_ln1), *h3 = (bf16*)sym(g_h3);
  GemmMaps gm;
  map_a(&gm.a[0], xn2, D_); map_a(&gm.a[1], h1, D_); map_a(&gm.a[2], ln1, D_); map_a(&gm.a[3], h3, F_); map_a(&gm.a[4], ox, 4096);
  map_w(&gm.b[0], w1, D_, D_); map_w(&gm.b[1], w2, D_, D_); map_w(&gm.b[2], w3, F_, D_); map_w(&gm.b[3], w4, D_, F_);
  map_w(&gm.b[4], Wo, D_, 4096);
  map_c(&gm.c[0], h1, D_); map_c(&gm.c[1], x1, D_); map_c(&gm.c[2], h3, F_); map_c(&gm.c[3], gate, D_); map_c(&gm.c[4], d_out, D_);
  map_c(&gm.c[5], ln1, D_);
  map_a(&gm.e[0], xn, D_); map_a(&gm.e[1], x1, D_); map_a(&gm.e[2], gate, D_); map_a(&gm.e[3], x, D_);
  map_w(&gm.od, ox, 4096, S_);
  RecMaps rm;
  for (int i = 0; i < 3; i++) {
    map2d(&rm.w[i], d_in[2 + i], 4096, D_, 64, 16, CU_TENSOR_MAP_SWIZZLE_128B);
    map2d(&rm.wb[i], d_in[2 + i], 4096, D_, 64, 256, CU_TENSOR_MAP_SWIZZLE_128B);
  }
  map2d(&rm.wo, Wo, D_, 4096, 64, 128, CU_TENSOR_MAP_SWIZZLE_128B);
  map2d(&rm.xn, xn, D_, S_, 64, 32, CU_TENSOR_MAP_SWIZZLE_128B);
  map_seg(&rm.xn1, xn, D_, 2, 1); map_seg(&rm.xn2, xn, D_, 2, 2);
  map2d(&rm.ox, ox, 4096, S_, 16, 32, CU_TENSOR_MAP_SWIZZLE_32B);
  unsigned char* xch = (unsigned char*)(((uintptr_t)sym(g_xch) + 2 * XPAGE - 1) & ~(uintptr_t)(2 * XPAGE - 1));
  cudaLaunchAttribute at[1];
  at[0].id = cudaLaunchAttributeClusterDimension;
  at[0].val.clusterDim.x = 6; at[0].val.clusterDim.y = 1; at[0].val.clusterDim.z = 1;
  cudaLaunchConfig_t cfg = {};
  cfg.attrs = at; cfg.numAttrs = 1; cfg.stream = cudaStreamPerThread;
  cfg.gridDim = dim3(96); cfg.blockDim = dim3(384); cfg.dynamicSmemBytes = R_SMEM;
  cudaLaunchKernelEx(&cfg, k_rec, rm, x, mem0, xch);
  at[0].id = cudaLaunchAttributeProgrammaticStreamSerialization;
  at[0].val.programmaticStreamSerializationAllowed = 1;
  cfg.gridDim = dim3(2 * NPAIR); cfg.dynamicSmemBytes = G_SMEM;
  cudaLaunchKernelEx(&cfg, k_gemm, gm, x, (bf16*)d_out);
}
```

```cpp
#include <cuda_runtime.h>
#include <cuda_bf16.h>
#include <cuda.h>
#include <stdint.h>

typedef __nv_bfloat16 bf16;

constexpr int S_ = 2048, D_ = 1024, H_ = 32, DH_ = 128, F_ = 3584, NSEG = 64;

__device__ __align__(1024) bf16 g_xn[S_ * D_];
__device__ __align__(1024) bf16 g_xn2[S_ * D_];
__device__ __align__(1024) bf16 g_ox[S_ * H_ * DH_];
__device__ __align__(1024) bf16 g_h1[S_ * D_];
__device__ __align__(1024) bf16 g_x1[S_ * D_];
__device__ __align__(1024) bf16 g_ln1[S_ * D_];
__device__ __align__(1024) bf16 g_h3[S_ * F_];
__device__ __align__(1024) bf16 g_gate[S_ * D_];
__device__ __align__(1024) uint4 g_dx[32 * 16 * 512];
__device__ __align__(1024) uint2 g_rstat[S_ * 4];

constexpr int XPAGE = 1 << 21;
__device__ __align__(4096) unsigned char g_xch[4 * XPAGE];
__device__ __forceinline__ uint32_t xchunk(int c, int p) { return (uint32_t)(c | ((__popc(c & 0xb3) & 1) ^ p)) << 12; }

#define TR(i)
#define TRB(i)
#define TRX(i, v)
#define TRV(i, v)
#define TG(r, i)
#define TRCAL(k)
#define ST(i)
__device__ __forceinline__ uint32_t smem_u32(const void* p) { return (uint32_t)__cvta_generic_to_shared(p); }
__device__ __forceinline__ void mbar_init(uint32_t bar, int cnt) {
  asm volatile("mbarrier.init.shared::cta.b64 [%0], %1;" ::"r"(bar), "r"(cnt) : "memory");
}
__device__ __forceinline__ void mbar_expect_tx(uint32_t bar, int bytes) {
  asm volatile("mbarrier.arrive.expect_tx.shared::cta.b64 _, [%0], %1;" ::"r"(bar), "r"(bytes) : "memory");
}
__device__ __forceinline__ void mbar_arrive(uint32_t bar) {
  asm volatile("mbarrier.arrive.shared::cta.b64 _, [%0];" ::"r"(bar) : "memory");
}
__device__ __forceinline__ void mbar_wait(uint32_t bar, uint32_t parity) {
  uint32_t ok;
  int n = 0;
  do {
    asm volatile(
        "{.reg .pred p; mbarrier.try_wait.parity.shared::cta.b64 p, [%1], %2; selp.u32 %0, 1, 0, p;}"
        : "=r"(ok) : "r"(bar), "r"(parity) : "memory");
  } while (!ok && ++n < (1 << 22));
}
__device__ __forceinline__ void mbar_wait_long(uint32_t bar, uint32_t parity) {
  uint32_t ok;
  int n = 0;
#pragma unroll 1
  do {
    asm volatile(
        "{.reg .pred p; mbarrier.try_wait.parity.shared::cta.b64 p, [%1], %2, 2000; selp.u32 %0, 1, 0, p;}"
        : "=r"(ok) : "r"(bar), "r"(parity) : "memory");
  } while (!ok && ++n < (1 << 22));
}
__device__ __forceinline__ void tma_load_2d(uint32_t dst, const CUtensorMap* m, int c0, int c1, uint32_t bar) {
  asm volatile(
      "cp.async.bulk.tensor.2d.shared::cluster.global.mbarrier::complete_tx::bytes [%0], [%1, {%3, %4}], [%2];"
      ::"r"(dst), "l"(m), "r"(bar), "r"(c0), "r"(c1) : "memory");
}
__device__ __forceinline__ void tma_load_2d_ef(uint32_t dst, const CUtensorMap* m, int c0, int c1, uint32_t bar) {
  asm volatile(
      "{.reg .b64 pol; createpolicy.fractional.L2::evict_first.b64 pol, 1.0;\n"
      "cp.async.bulk.tensor.2d.shared::cluster.global.mbarrier::complete_tx::bytes.L2::cache_hint [%0], [%1, {%3, %4}], [%2], pol;}"
      ::"r"(dst), "l"(m), "r"(bar), "r"(c0), "r"(c1) : "memory");
}
__device__ __forceinline__ void tma_load_3d(uint32_t dst, const CUtensorMap* m, int c0, int c1, int c2, uint32_t bar) {
  asm volatile(
      "cp.async.bulk.tensor.3d.shared::cluster.global.mbarrier::complete_tx::bytes [%0], [%1, {%3, %4, %5}], [%2];"
      ::"r"(dst), "l"(m), "r"(bar), "r"(c0), "r"(c1), "r"(c2) : "memory");
}
__device__ __forceinline__ void tma_store_2d(const CUtensorMap* m, uint32_t src, int c0, int c1) {
  asm volatile("cp.async.bulk.tensor.2d.global.shared::cta.bulk_group [%0, {%2, %3}], [%1];"
               ::"l"(m), "r"(src), "r"(c0), "r"(c1) : "memory");
}
__device__ __forceinline__ uint64_t policy(bool stream) {
  uint64_t a, b;
  asm("createpolicy.fractional.L2::evict_first.b64 %0, 1.0;" : "=l"(a));
  asm("createpolicy.fractional.L2::evict_normal.b64 %0, 1.0;" : "=l"(b));
  return stream ? a : b;
}
__device__ __forceinline__ void tma_store_2d_p(const CUtensorMap* m, uint32_t src, int c0, int c1, uint64_t pol) {
  asm volatile("cp.async.bulk.tensor.2d.global.shared::cta.bulk_group.L2::cache_hint [%0, {%2, %3}], [%1], %4;"
               ::"l"(m), "r"(src), "r"(c0), "r"(c1), "l"(pol) : "memory");
}
__device__ __forceinline__ void tma_prefetch_2d(const CUtensorMap* m, int c0, int c1) {
  asm volatile("cp.async.bulk.prefetch.tensor.2d.L2.global [%0, {%1, %2}];" ::"l"(m), "r"(c0), "r"(c1) : "memory");
}
__device__ __forceinline__ void tma_prefetch_3d(const CUtensorMap* m, int c0, int c1, int c2) {
  asm volatile("cp.async.bulk.prefetch.tensor.3d.L2.global [%0, {%1, %2, %3}];" ::"l"(m), "r"(c0), "r"(c1), "r"(c2) : "memory");
}
__device__ __forceinline__ uint32_t clk32() { uint32_t c; asm volatile("mov.u32 %0, %%clock;" : "=r"(c)::"memory"); return c; }
__device__ __forceinline__ uint32_t ld_rlx1(const void* p) { uint32_t v; asm volatile("ld.relaxed.gpu.global.u32 %0, [%1];" : "=r"(v) : "l"(p) : "memory"); return v; }
__device__ __forceinline__ uint32_t smid() { uint32_t c; asm volatile("mov.u32 %0, %%smid;" : "=r"(c)); return c; }
__device__ __forceinline__ void fence_async_smem() { asm volatile("fence.proxy.async.shared::cta;" ::: "memory"); }
__device__ __forceinline__ void bar_sync(int id, int n) { asm volatile("bar.sync %0, %1;" ::"r"(id), "r"(n) : "memory"); }
__device__ __forceinline__ void bar_arrive(int id, int n) { asm volatile("bar.arrive %0, %1;" ::"r"(id), "r"(n) : "memory"); }
__host__ __device__ constexpr uint64_t make_desc(uint32_t addr, uint32_t lbo, uint32_t sbo, uint32_t mode) {
  return (uint64_t)((addr & 0x3FFFF) >> 4) | ((uint64_t)(lbo >> 4) << 16) | ((uint64_t)(sbo >> 4) << 32) |
         ((uint64_t)mode << 62);
}
#define WG_FENCE() asm volatile("wgmma.fence.sync.aligned;" ::: "memory")
#define WG_COMMIT() asm volatile("wgmma.commit_group.sync.aligned;" ::: "memory")
#define WG_WAIT(n) asm volatile("wgmma.wait_group.sync.aligned " #n ";" ::: "memory")

__device__ __forceinline__ uint32_t pack_bf16(float lo, float hi) {
  uint32_t r;
  asm("cvt.rn.bf16x2.f32 %0, %1, %2;" : "=r"(r) : "f"(hi), "f"(lo));
  return r;
}
__device__ __forceinline__ float bf_lo(uint32_t v) { return __uint_as_float(v << 16); }
__device__ __forceinline__ float bf_hi(uint32_t v) { return __uint_as_float(v & 0xffff0000u); }
__device__ __forceinline__ float rbf(float x) { return __bfloat162float(__float2bfloat16_rn(x)); }

__device__ __forceinline__ void ldsm4(uint32_t* r, uint32_t a) {
  asm volatile("ldmatrix.sync.aligned.m8n8.x4.shared.b16 {%0,%1,%2,%3}, [%4];"
               : "=r"(r[0]), "=r"(r[1]), "=r"(r[2]), "=r"(r[3]) : "r"(a) : "memory");
}
__device__ __forceinline__ void ldsm4t(uint32_t* r, uint32_t a) {
  asm volatile("ldmatrix.sync.aligned.m8n8.x4.trans.shared.b16 {%0,%1,%2,%3}, [%4];"
               : "=r"(r[0]), "=r"(r[1]), "=r"(r[2]), "=r"(r[3]) : "r"(a) : "memory");
}
__device__ __forceinline__ void stsm4(uint32_t a, uint32_t r0, uint32_t r1, uint32_t r2, uint32_t r3) {
  asm volatile("stmatrix.sync.aligned.m8n8.x4.shared.b16 [%0], {%1,%2,%3,%4};"
               ::"r"(a), "r"(r0), "r"(r1), "r"(r2), "r"(r3) : "memory");
}
__device__ __forceinline__ void stsm4t(uint32_t a, uint32_t r0, uint32_t r1, uint32_t r2, uint32_t r3) {
  asm volatile("stmatrix.sync.aligned.m8n8.x4.trans.shared.b16 [%0], {%1,%2,%3,%4};"
               ::"r"(a), "r"(r0), "r"(r1), "r"(r2), "r"(r3) : "memory");
}
__device__ __forceinline__ void mma16816(float* d, uint32_t a0, uint32_t a1, uint32_t a2, uint32_t a3, uint32_t b0,
                                         uint32_t b1) {
  asm(
      "mma.sync.aligned.m16n8k16.row.col.f32.bf16.bf16.f32 {%0,%1,%2,%3}, {%4,%5,%6,%7}, {%8,%9}, {%0,%1,%2,%3};"
      : "+f"(d[0]), "+f"(d[1]), "+f"(d[2]), "+f"(d[3]) : "r"(a0), "r"(a1), "r"(a2), "r"(a3), "r"(b0), "r"(b1));
}
__device__ __forceinline__ void mma16816c(float* d, const float* c, uint32_t a0, uint32_t a1, uint32_t a2, uint32_t a3,
                                          uint32_t b0, uint32_t b1) {
  asm volatile(
      "mma.sync.aligned.m16n8k16.row.col.f32.bf16.bf16.f32 {%0,%1,%2,%3}, {%4,%5,%6,%7}, {%8,%9}, {%10,%11,%12,%13};"
      : "=f"(d[0]), "=f"(d[1]), "=f"(d[2]), "=f"(d[3])
      : "r"(a0), "r"(a1), "r"(a2), "r"(a3), "r"(b0), "r"(b1), "f"(c[0]), "f"(c[1]), "f"(c[2]), "f"(c[3]));
}
__device__ __forceinline__ void mma1688(float* d, uint32_t a0, uint32_t a1, uint32_t b0) {
  asm("mma.sync.aligned.m16n8k8.row.col.f32.bf16.bf16.f32 {%0,%1,%2,%3}, {%4,%5}, {%6}, {%0,%1,%2,%3};"
               : "+f"(d[0]), "+f"(d[1]), "+f"(d[2]), "+f"(d[3]) : "r"(a0), "r"(a1), "r"(b0));
}
__device__ __forceinline__ void wgmma_n8_tt(float* d, uint64_t a, uint64_t b, int scale_d) {
  asm volatile(
      "{.reg .pred p; setp.ne.b32 p, %6, 0;\n"
      "wgmma.mma_async.sync.aligned.m64n8k16.f32.bf16.bf16 {%0,%1,%2,%3}, %4, %5, p, 1, 1, 1, 1;}"
      : "+f"(d[0]), "+f"(d[1]), "+f"(d[2]), "+f"(d[3]) : "l"(a), "l"(b), "r"(scale_d));
}
__device__ __forceinline__ void wgmma_n256(float* d, uint64_t a, uint64_t b, int scale_d) {
  asm volatile(
      "{.reg .pred p; setp.ne.b32 p, %130, 0;\n"
      "wgmma.mma_async.sync.aligned.m64n256k16.f32.bf16.bf16 "
      "{%0,%1,%2,%3,%4,%5,%6,%7,%8,%9,%10,%11,%12,%13,%14,%15,%16,%17,%18,%19,%20,%21,%22,%23,%24,%25,%26,%27,%28,%29,%30,%31,"
      "%32,%33,%34,%35,%36,%37,%38,%39,%40,%41,%42,%43,%44,%45,%46,%47,%48,%49,%50,%51,%52,%53,%54,%55,%56,%57,%58,%59,%60,%61,%62,%63,"
      "%64,%65,%66,%67,%68,%69,%70,%71,%72,%73,%74,%75,%76,%77,%78,%79,%80,%81,%82,%83,%84,%85,%86,%87,%88,%89,%90,%91,%92,%93,%94,%95,"
      "%96,%97,%98,%99,%100,%101,%102,%103,%104,%105,%106,%107,%108,%109,%110,%111,%112,%113,%114,%115,%116,%117,%118,%119,%120,%121,%122,%123,%124,%125,%126,%127},"
      " %128, %129, p, 1, 1, 0, 1;}"
      : "+f"(d[0]), "+f"(d[1]), "+f"(d[2]), "+f"(d[3]), "+f"(d[4]), "+f"(d[5]), "+f"(d[6]), "+f"(d[7]),
        "+f"(d[8]), "+f"(d[9]), "+f"(d[10]), "+f"(d[11]), "+f"(d[12]), "+f"(d[13]), "+f"(d[14]), "+f"(d[15]),
        "+f"(d[16]), "+f"(d[17]), "+f"(d[18]), "+f"(d[19]), "+f"(d[20]), "+f"(d[21]), "+f"(d[22]), "+f"(d[23]),
        "+f"(d[24]), "+f"(d[25]), "+f"(d[26]), "+f"(d[27]), "+f"(d[28]), "+f"(d[29]), "+f"(d[30]), "+f"(d[31]),
        "+f"(d[32]), "+f"(d[33]), "+f"(d[34]), "+f"(d[35]), "+f"(d[36]), "+f"(d[37]), "+f"(d[38]), "+f"(d[39]),
        "+f"(d[40]), "+f"(d[41]), "+f"(d[42]), "+f"(d[43]), "+f"(d[44]), "+f"(d[45]), "+f"(d[46]), "+f"(d[47]),
        "+f"(d[48]), "+f"(d[49]), "+f"(d[50]), "+f"(d[51]), "+f"(d[52]), "+f"(d[53]), "+f"(d[54]), "+f"(d[55]),
        "+f"(d[56]), "+f"(d[57]), "+f"(d[58]), "+f"(d[59]), "+f"(d[60]), "+f"(d[61]), "+f"(d[62]), "+f"(d[63]),
        "+f"(d[64]), "+f"(d[65]), "+f"(d[66]), "+f"(d[67]), "+f"(d[68]), "+f"(d[69]), "+f"(d[70]), "+f"(d[71]),
        "+f"(d[72]), "+f"(d[73]), "+f"(d[74]), "+f"(d[75]), "+f"(d[76]), "+f"(d[77]), "+f"(d[78]), "+f"(d[79]),
        "+f"(d[80]), "+f"(d[81]), "+f"(d[82]), "+f"(d[83]), "+f"(d[84]), "+f"(d[85]), "+f"(d[86]), "+f"(d[87]),
        "+f"(d[88]), "+f"(d[89]), "+f"(d[90]), "+f"(d[91]), "+f"(d[92]), "+f"(d[93]), "+f"(d[94]), "+f"(d[95]),
        "+f"(d[96]), "+f"(d[97]), "+f"(d[98]), "+f"(d[99]), "+f"(d[100]), "+f"(d[101]), "+f"(d[102]), "+f"(d[103]),
        "+f"(d[104]), "+f"(d[105]), "+f"(d[106]), "+f"(d[107]), "+f"(d[108]), "+f"(d[109]), "+f"(d[110]), "+f"(d[111]),
        "+f"(d[112]), "+f"(d[113]), "+f"(d[114]), "+f"(d[115]), "+f"(d[116]), "+f"(d[117]), "+f"(d[118]), "+f"(d[119]),
        "+f"(d[120]), "+f"(d[121]), "+f"(d[122]), "+f"(d[123]), "+f"(d[124]), "+f"(d[125]), "+f"(d[126]), "+f"(d[127])
      : "l"(a), "l"(b), "r"(scale_d));
}

__device__ __forceinline__ uint4 ld_rlx4(const void* p) {
  uint4 v;
  asm volatile("{.reg .b128 r; ld.relaxed.gpu.global.b128 r, [%4]; mov.b128 {%0,%1,%2,%3}, r;}"
               : "=r"(v.x), "=r"(v.y), "=r"(v.z), "=r"(v.w) : "l"(p) : "memory");
  return v;
}
__device__ __forceinline__ uint2 ld_rlx2(const void* p) {
  uint2 v;
  asm volatile("{.reg .b64 r; ld.relaxed.gpu.global.b64 r, [%2]; mov.b64 {%0,%1}, r;}" : "=r"(v.x), "=r"(v.y) : "l"(p) : "memory");
  return v;
}
__device__ __forceinline__ void st_rlx4(void* p, uint32_t a, uint32_t b, uint32_t c, uint32_t d) {
  asm volatile("{.reg .b128 r; mov.b128 r, {%1,%2,%3,%4}; st.relaxed.gpu.global.b128 [%0], r;}"
               ::"l"(p), "r"(a), "r"(b), "r"(c), "r"(d) : "memory");
}
__device__ __forceinline__ void st_rlx2(void* p, uint32_t a, uint32_t b) {
  asm volatile("{.reg .b64 r; mov.b64 r, {%1,%2}; st.relaxed.gpu.global.b64 [%0], r;}" ::"l"(p), "r"(a), "r"(b) : "memory");
}
__device__ __forceinline__ void st_rlx1(void* p, uint32_t a) {
  asm volatile("st.relaxed.gpu.global.u32 [%0], %1;" ::"l"(p), "r"(a) : "memory");
}

__device__ __forceinline__ uint32_t nz(uint32_t v) { return v == 0u ? 0x80000000u : v; }
__device__ __forceinline__ uint32_t tagu(uint32_t v, uint32_t tag) { return (v & ~1u) | tag; }
__device__ __forceinline__ float asf(uint32_t v) { return __uint_as_float(v); }
__device__ __forceinline__ uint32_t asu(float v) { return __float_as_uint(v); }
__device__ __forceinline__ uint32_t opaque(uint32_t x) { return __shfl_sync(~0u, x, threadIdx.x & 31); }
__device__ __forceinline__ unsigned char* xptr(uint32_t lo, uint32_t hi) {
  uint64_t a;
  asm("mov.b64 %0, {%1, %2};" : "=l"(a) : "r"(lo), "r"(hi));
  return (unsigned char*)a;
}
#define DSC(lo) (uint64_t)xptr(lo, (uint32_t)(make_desc(0, 0, 1024, 1) >> 32))
__device__ __forceinline__ void reld4(uint4& v, const void* p, uint32_t m) {
  asm volatile("{.reg .pred q; setp.eq.b32 q, %5, 0; @q ld.relaxed.gpu.global.v4.b32 {%0,%1,%2,%3}, [%4];}"
               : "+r"(v.x), "+r"(v.y), "+r"(v.z), "+r"(v.w) : "l"(p), "r"(m) : "memory");
}
__device__ __forceinline__ uint32_t ne2(uint32_t a, uint32_t b, uint32_t t) {
  uint32_t r;
  asm("lop3.b32 %0, %1, %2, %3, 0x7E;" : "=r"(r) : "r"(a), "r"(b), "r"(t));
  return r;
}
__device__ __forceinline__ uint32_t or3(uint32_t a, uint32_t b, uint32_t c) {
  uint32_t r;
  asm("lop3.b32 %0, %1, %2, %3, 0xFE;" : "=r"(r) : "r"(a), "r"(b), "r"(c));
  return r;
}
__device__ __forceinline__ uint32_t after(uint32_t a, uint32_t dep, uint32_t zero) {
  uint32_t r;
  asm("lop3.b32 %0, %1, %2, %3, 0xF8;" : "=r"(r) : "r"(a), "r"(dep), "r"(zero));
  return r;
}
__device__ __forceinline__ uint32_t wait_clk(uint32_t t, int D) {
  uint32_t c = clk32();
  if ((int)(t - c) < D) t = c + D;
  while ((int)(c - t) < 0) c = clk32();
  return c;
}
__device__ __forceinline__ uint2 timer_edge() {
  uint32_t g0, g;
  int n = 0;
  asm volatile("mov.u32 %0, %%globaltimer_lo;" : "=r"(g0)::"memory");
#pragma unroll 1
  do { asm volatile("mov.u32 %0, %%globaltimer_lo;" : "=r"(g)::"memory"); } while (g == g0 && ++n < 8);
  return make_uint2(g, clk32());
}
__device__ __forceinline__ float4 lds_f4(uint32_t a) {
  float4 v;
  asm volatile("ld.shared.v4.f32 {%0,%1,%2,%3}, [%4];" : "=f"(v.x), "=f"(v.y), "=f"(v.z), "=f"(v.w) : "r"(a) : "memory");
  return v;
}
__device__ __forceinline__ uint4 lds_u4(uint32_t a) {
  uint4 v;
  asm volatile("ld.shared.v4.u32 {%0,%1,%2,%3}, [%4];" : "=r"(v.x), "=r"(v.y), "=r"(v.z), "=r"(v.w) : "r"(a) : "memory");
  return v;
}
__device__ __forceinline__ uint2 lds_u2(uint32_t a) {
  uint2 v;
  asm volatile("ld.shared.v2.u32 {%0,%1}, [%2];" : "=r"(v.x), "=r"(v.y) : "r"(a) : "memory");
  return v;
}
__device__ __forceinline__ uint32_t lds_u1(uint32_t a) {
  uint32_t v;
  asm volatile("ld.shared.u32 %0, [%1];" : "=r"(v) : "r"(a) : "memory");
  return v;
}
__device__ __forceinline__ void sts_u4(uint32_t a, uint4 v) {
  asm volatile("st.shared.v4.u32 [%0], {%1,%2,%3,%4};" ::"r"(a), "r"(v.x), "r"(v.y), "r"(v.z), "r"(v.w) : "memory");
}
__device__ __forceinline__ void sts_f4(uint32_t a, const float* d) {
  asm volatile("st.shared.v4.f32 [%0], {%1,%2,%3,%4};" ::"r"(a), "f"(d[0]), "f"(d[1]), "f"(d[2]), "f"(d[3]) : "memory");
}
__device__ __forceinline__ void sts_u2(uint32_t a, uint32_t x, uint32_t y) {
  asm volatile("st.shared.v2.u32 [%0], {%1,%2};" ::"r"(a), "r"(x), "r"(y) : "memory");
}
__device__ __forceinline__ void sts_u1(uint32_t a, uint32_t v) {
  asm volatile("st.shared.u32 [%0], %1;" ::"r"(a), "r"(v) : "memory");
}
__device__ __forceinline__ void sta4(uint32_t a, uint4 v, uint32_t bar) {
  asm volatile("st.async.shared::cluster.mbarrier::complete_tx::bytes.v4.b32 [%0], {%1,%2,%3,%4}, [%5];"
               ::"r"(a), "r"(v.x), "r"(v.y), "r"(v.z), "r"(v.w), "r"(bar) : "memory");
}
__device__ __forceinline__ void sta2(uint32_t a, uint32_t x, uint32_t y, uint32_t bar) {
  asm volatile("st.async.shared::cluster.mbarrier::complete_tx::bytes.v2.b32 [%0], {%1,%2}, [%3];" ::"r"(a), "r"(x), "r"(y), "r"(bar) : "memory");
}
__device__ __forceinline__ void sta1(uint32_t a, uint32_t x, uint32_t bar) {
  asm volatile("st.async.shared::cluster.mbarrier::complete_tx::bytes.b32 [%0], %1, [%2];" ::"r"(a), "r"(x), "r"(bar) : "memory");
}
__device__ __forceinline__ void arrive_remote(uint32_t bar) {
  asm volatile("mbarrier.arrive.shared::cluster.b64 _, [%0];" ::"r"(bar) : "memory");
}
__device__ __forceinline__ uint32_t peer_base(uint32_t sb, int rank) {
  uint32_t r;
  asm("mapa.shared::cluster.u32 %0, %1, %2;" : "=r"(r) : "r"(sb), "r"(rank));
  return r - sb;
}
__device__ __forceinline__ float ex2(float x) { float r; asm("ex2.approx.ftz.f32 %0, %1;" : "=f"(r) : "f"(x)); return r; }
__device__ __forceinline__ float rcp(float x) { float r; asm("rcp.approx.ftz.f32 %0, %1;" : "=f"(r) : "f"(x)); return r; }
__device__ __forceinline__ uint32_t min4(uint4 v) { return min(__vimin3_u32(v.x, v.y, v.z), v.w); }

__device__ __forceinline__ void softmax_e(float* sc) {
  float mx = fmaxf(fmaxf(fmaxf(sc[0], sc[1]), fmaxf(sc[2], sc[3])), fmaxf(fmaxf(sc[4], sc[5]), fmaxf(sc[6], sc[7])));
  mx = fmaxf(mx, fmaxf(sc[8], sc[9]));
  const float m1 = __shfl_xor_sync(~0u, mx, 1), m2 = __shfl_xor_sync(~0u, mx, 2), m3 = __shfl_xor_sync(~0u, mx, 3);
  mx = fmaxf(fmaxf(mx, m1), fmaxf(m2, m3));
  const float c = 0.08838834764831845f * 1.4426950408889634f, mc = -mx * c;
#pragma unroll
  for (int i = 0; i < 10; i++) sc[i] = ex2(fmaf(sc[i], c, mc));
}
__device__ __forceinline__ void sum_scores(float* sc, uint2 u0, uint2 u1, uint32_t u2, uint2 v0, uint2 v1, uint32_t v2) {
  sc[0] = bf_lo(u0.x) + bf_lo(v0.x); sc[1] = bf_hi(u0.x) + bf_hi(v0.x);
  sc[2] = bf_lo(u0.y) + bf_lo(v0.y); sc[3] = bf_hi(u0.y) + bf_hi(v0.y);
  sc[4] = bf_lo(u1.x) + bf_lo(v1.x); sc[5] = bf_hi(u1.x) + bf_hi(v1.x);
  sc[6] = bf_lo(u1.y) + bf_lo(v1.y); sc[7] = bf_hi(u1.y) + bf_hi(v1.y);
  sc[8] = bf_lo(u2) + bf_lo(v2); sc[9] = bf_hi(u2) + bf_hi(v2);
}
__device__ __forceinline__ void pv_mma(float* o0, float* o1, float* sm, const uint4* vx, const uint2* m, const uint32_t* p) {
  const uint32_t one = 0x3F803F80u;
#pragma unroll
  for (int i = 0; i < 4; i++) o0[i] = o1[i] = sm[i] = 0.f;
  mma16816(sm, one, one, one, one, p[0], p[1]);
  mma16816(o0, vx[0].x, vx[0].y, vx[0].z, vx[0].w, p[0], p[1]);
  mma16816(o1, vx[1].x, vx[1].y, vx[1].z, vx[1].w, p[0], p[1]);
  mma16816(sm, one, one, one, one, p[2], p[3]);
  mma16816(o0, vx[2].x, vx[2].y, vx[2].z, vx[2].w, p[2], p[3]);
  mma16816(o1, vx[3].x, vx[3].y, vx[3].z, vx[3].w, p[2], p[3]);
  mma1688(sm, one, one, p[4]);
  mma16816(o0, m[0].x, m[0].y, m[1].x, m[1].y, p[4], p[4]);
  mma16816(o1, m[2].x, m[2].y, m[3].x, m[3].y, p[4], p[4]);
}
#define D16(d) "+f"(d[0]), "+f"(d[1]), "+f"(d[2]), "+f"(d[3]), "+f"(d[4]), "+f"(d[5]), "+f"(d[6]), "+f"(d[7]), "+f"(d[8]), \
               "+f"(d[9]), "+f"(d[10]), "+f"(d[11]), "+f"(d[12]), "+f"(d[13]), "+f"(d[14]), "+f"(d[15])
__device__ __forceinline__ void wgmma_rs32(float* d, const uint32_t* a, uint64_t b, int scale_d) {
  asm volatile(
      "{.reg .pred p; setp.ne.b32 p, %21, 0;\n"
      "wgmma.mma_async.sync.aligned.m64n32k16.f32.bf16.bf16 {%0,%1,%2,%3,%4,%5,%6,%7,%8,%9,%10,%11,%12,%13,%14,%15}, "
      "{%16,%17,%18,%19}, %20, p, 1, 1, 0;}"
      : D16(d) : "r"(a[0]), "r"(a[1]), "r"(a[2]), "r"(a[3]), "l"(b), "r"(scale_d));
}
__device__ __forceinline__ void wgmma_ss32(float* d, uint64_t a, uint64_t b, int scale_d) {
  asm volatile(
      "{.reg .pred p; setp.ne.b32 p, %18, 0;\n"
      "wgmma.mma_async.sync.aligned.m64n32k16.f32.bf16.bf16 {%0,%1,%2,%3,%4,%5,%6,%7,%8,%9,%10,%11,%12,%13,%14,%15}, "
      "%16, %17, p, 1, 1, 1, 0;}"
      : D16(d) : "l"(a), "l"(b), "r"(scale_d));
}
#define R32 "{%0,%1,%2,%3,%4,%5,%6,%7,%8,%9,%10,%11,%12,%13,%14,%15,%16,%17,%18,%19,%20,%21,%22,%23,%24,%25,%26,%27,%28,%29,%30,%31}, "
__device__ __forceinline__ void wgmma_rs64(float* d, const uint32_t* a, uint64_t b, int scale_d) {
  asm volatile("{.reg .pred p; setp.ne.b32 p, %37, 0;\nwgmma.mma_async.sync.aligned.m64n64k16.f32.bf16.bf16 " R32 "{%32,%33,%34,%35}, %36, p, 1, 1, 0;}"
               : D16(d), D16((d + 16)) : "r"(a[0]), "r"(a[1]), "r"(a[2]), "r"(a[3]), "l"(b), "r"(scale_d));
}
__device__ __forceinline__ void wgmma_ss64(float* d, uint64_t a, uint64_t b) {
  asm volatile("wgmma.mma_async.sync.aligned.m64n64k16.f32.bf16.bf16 " R32 "%32, %33, 1, 1, 1, 1, 0;" : D16(d), D16((d + 16)) : "l"(a), "l"(b));
}
__device__ __forceinline__ void wgmma_ss48(float* d, uint64_t a, uint64_t b, int scale_d) {
  asm volatile(
      "{.reg .pred p; setp.ne.b32 p, %26, 0;\n"
      "wgmma.mma_async.sync.aligned.m64n48k16.f32.bf16.bf16 {%0,%1,%2,%3,%4,%5,%6,%7,%8,%9,%10,%11,%12,%13,%14,%15,"
      "%16,%17,%18,%19,%20,%21,%22,%23}, %24, %25, p, 1, 1, 0, 0;}"
      : D16(d), "+f"(d[16]), "+f"(d[17]), "+f"(d[18]), "+f"(d[19]), "+f"(d[20]), "+f"(d[21]), "+f"(d[22]), "+f"(d[23])
      : "l"(a), "l"(b), "r"(scale_d));
}
enum { T_W1, T_W2, T_W3, T_W4, T_WO, T_LN };
constexpr int NPAIR = 18, G_STAGES = 4, G_STAGE_BYTES = 49152, G_STG = G_STAGES * G_STAGE_BYTES, G_BAR = G_STG + 32768,
              G_SMEM = G_BAR + 512;
constexpr int WAIT_LIM = 1 << 22;
#define NSLP 40
enum { C_H1 = 0, C_LN1 = 16, C_H3 = 32, C_G = 48, C_OX = 64, C_LN = 128, C_CHK, C_DONE, C_END };
__device__ __align__(128) unsigned g_cnt[C_END * 8];

struct GemmMaps { CUtensorMap a[5], b[5], c[6], e[4], od; };
__constant__ unsigned short c_list[2 * NPAIR][24] = {
    {0x1010, 0x1160, 0x121, 0xd1, 0x612, 0x432, 0x132, 0x4a2, 0x72, 0xf2, 0x3d2, 0x43, 0xe3, 0x873, 0x8000, 0x8000, 0x8000, 0x8000, 0x8000, 0x8000, 0x8000, 0x8000, 0x8000, 0x30},
    {0x1018, 0x1168, 0x129, 0xd9, 0x61a, 0x43a, 0x13a, 0x4aa, 0x7a, 0xfa, 0x3da, 0x4b, 0xeb, 0x87b, 0x8000, 0x8000, 0x8000, 0x8000, 0x8000, 0x8000, 0x8000, 0x8000, 0x8000, 0x30},
    {0x1190, 0x8d0, 0x131, 0x1192, 0x22, 0xc2, 0x4b2, 0x3c2, 0x252, 0x3e2, 0x23, 0x1a3, 0x944, 0x8000, 0x8000, 0x8000, 0x8000, 0x8000, 0x8000, 0x8000, 0x8000, 0x8000, 0x8000, 0x30},
    {0x1198, 0x8d8, 0x139, 0x119a, 0x2a, 0xca, 0x4ba, 0x3ca, 0x25a, 0x3ea, 0x2b, 0x1ab, 0x94c, 0x8000, 0x8000, 0x8000, 0x8000, 0x8000, 0x8000, 0x8000, 0x8000, 0x8000, 0x8000, 0x30},
    {0x40, 0x1050, 0x101, 0x1c1, 0x12, 0x3a2, 0x482, 0x2b2, 0x6d2, 0x462, 0x13, 0xb4, 0x9c4, 0x8000, 0x8000, 0x8000, 0x8000, 0x8000, 0x8000, 0x8000, 0x8000, 0x8000, 0x8000, 0x30},
    {0x48, 0x1058, 0x109, 0x1c9, 0x1a, 0x3aa, 0x48a, 0x2ba, 0x6da, 0x46a, 0x1b, 0xbc, 0x9cc, 0x8000, 0x8000, 0x8000, 0x8000, 0x8000, 0x8000, 0x8000, 0x8000, 0x8000, 0x8000, 0x30},
    {0x820, 0x991, 0x71, 0x2a2, 0x232, 0x422, 0x1262, 0x162, 0x152, 0x33, 0x1e3, 0x894, 0x8000, 0x8000, 0x8000, 0x8000, 0x8000, 0x8000, 0x8000, 0x8000, 0x8000, 0x8000, 0x8000, 0x30},
    {0x828, 0x999, 0x79, 0x2aa, 0x23a, 0x42a, 0x126a, 0x16a, 0x15a, 0x3b, 0x1eb, 0x89c, 0x8000, 0x8000, 0x8000, 0x8000, 0x8000, 0x8000, 0x8000, 0x8000, 0x8000, 0x8000, 0x8000, 0x30},
    {0x11a0, 0x11f0, 0x1, 0x161, 0x92, 0x82, 0x572, 0x1e2, 0x642, 0x272, 0x123, 0x184, 0x804, 0x8000, 0x8000, 0x8000, 0x8000, 0x8000, 0x8000, 0x8000, 0x8000, 0x8000, 0x8000, 0x30},
    {0x11a8, 0x11f8, 0x9, 0x169, 0x9a, 0x8a, 0x57a, 0x1ea, 0x64a, 0x27a, 0x12b, 0x18c, 0x80c, 0x8000, 0x8000, 0x8000, 0x8000, 0x8000, 0x8000, 0x8000, 0x8000, 0x8000, 0x8000, 0x30},
    {0x1180, 0x1170, 0x21, 0xe1, 0x392, 0x622, 0x1b2, 0x142, 0x452, 0xd2, 0x1b3, 0x34, 0x844, 0x8000, 0x8000, 0x8000, 0x8000, 0x8000, 0x8000, 0x8000, 0x8000, 0x8000, 0x8000, 0x30},
    {0x1188, 0x1178, 0x29, 0xe9, 0x39a, 0x62a, 0x1ba, 0x14a, 0x45a, 0xda, 0x1bb, 0x3c, 0x84c, 0x8000, 0x8000, 0x8000, 0x8000, 0x8000, 0x8000, 0x8000, 0x8000, 0x8000, 0x8000, 0x30},
    {0x900, 0x8e0, 0x141, 0x512, 0x2, 0x542, 0x342, 0x582, 0x1d2, 0x6f2, 0xa3, 0x163, 0x2854, 0x8000, 0x8000, 0x8000, 0x8000, 0x8000, 0x8000, 0x8000, 0x8000, 0x8000, 0x8000, 0x30},
    {0x908, 0x8e8, 0x149, 0x51a, 0xa, 0x54a, 0x34a, 0x58a, 0x1da, 0x6fa, 0xab, 0x16b, 0x28d4, 0x8000, 0x8000, 0x8000, 0x8000, 0x8000, 0x8000, 0x8000, 0x8000, 0x8000, 0x8000, 0x30},
    {0x10a0, 0x950, 0xb1, 0x171, 0x222, 0x412, 0x6e2, 0xb2, 0x472, 0x2e2, 0x103, 0xd3, 0x994, 0x8000, 0x8000, 0x8000, 0x8000, 0x8000, 0x8000, 0x8000, 0x8000, 0x8000, 0x8000, 0x30},
    {0x10a8, 0x958, 0xb9, 0x179, 0x22a, 0x41a, 0x6ea, 0xba, 0x47a, 0x2ea, 0x10b, 0xdb, 0x99c, 0x8000, 0x8000, 0x8000, 0x8000, 0x8000, 0x8000, 0x8000, 0x8000, 0x8000, 0x8000, 0x30},
    {0x8b0, 0x891, 0x61, 0x522, 0x32, 0x5b2, 0x1a2, 0x5e2, 0x52, 0x1c3, 0x153, 0x9a4, 0x8000, 0x8000, 0x8000, 0x8000, 0x8000, 0x8000, 0x8000, 0x8000, 0x8000, 0x8000, 0x8000, 0x30},
    {0x8b8, 0x899, 0x69, 0x52a, 0x3a, 0x5ba, 0x1aa, 0x5ea, 0x5a, 0x1cb, 0x15b, 0x9ac, 0x8000, 0x8000, 0x8000, 0x8000, 0x8000, 0x8000, 0x8000, 0x8000, 0x8000, 0x8000, 0x8000, 0x30},
    {0x1120, 0x9c0, 0x1b1, 0x492, 0x602, 0x1682, 0x62, 0x5f2, 0x4d2, 0x662, 0xb3, 0x63, 0x8c4, 0x8000, 0x8000, 0x8000, 0x8000, 0x8000, 0x8000, 0x8000, 0x8000, 0x8000, 0x8000, 0x30},
    {0x1128, 0x9c8, 0x1b9, 0x49a, 0x60a, 0x168a, 0x6a, 0x5fa, 0x4da, 0x66a, 0xbb, 0x6b, 0x8cc, 0x8000, 0x8000, 0x8000, 0x8000, 0x8000, 0x8000, 0x8000, 0x8000, 0x8000, 0x8000, 0x30},
    {0x880, 0x811, 0x1e1, 0x692, 0x6a2, 0x332, 0x352, 0x3f2, 0x672, 0x3, 0xc3, 0x914, 0x8000, 0x8000, 0x8000, 0x8000, 0x8000, 0x8000, 0x8000, 0x8000, 0x8000, 0x8000, 0x8000, 0x30},
    {0x888, 0x819, 0x1e9, 0x69a, 0x6aa, 0x33a, 0x35a, 0x3fa, 0x67a, 0xb, 0xcb, 0x91c, 0x8000, 0x8000, 0x8000, 0x8000, 0x8000, 0x8000, 0x8000, 0x8000, 0x8000, 0x8000, 0x8000, 0x30},
    {0x930, 0x911, 0x1f1, 0x182, 0x242, 0x202, 0x362, 0x5d2, 0x552, 0x183, 0xf3, 0x884, 0x8000, 0x8000, 0x8000, 0x8000, 0x8000, 0x8000, 0x8000, 0x8000, 0x8000, 0x8000, 0x8000, 0x30},
    {0x938, 0x919, 0x1f9, 0x18a, 0x24a, 0x20a, 0x36a, 0x5da, 0x55a, 0x18b, 0xfb, 0x88c, 0x8000, 0x8000, 0x8000, 0x8000, 0x8000, 0x8000, 0x8000, 0x8000, 0x8000, 0x8000, 0x8000, 0x30},
    {0x1030, 0x1060, 0x1a1, 0x51, 0x212, 0x302, 0x1c2, 0x6b2, 0x2f2, 0x4e2, 0x133, 0x1b4, 0x924, 0x8000, 0x8000, 0x8000, 0x8000, 0x8000, 0x8000, 0x8000, 0x8000, 0x8000, 0x8000, 0x30},
    {0x1038, 0x1068, 0x1a9, 0x59, 0x21a, 0x30a, 0x1ca, 0x6ba, 0x2fa, 0x4ea, 0x13b, 0x1bc, 0x92c, 0x8000, 0x8000, 0x8000, 0x8000, 0x8000, 0x8000, 0x8000, 0x8000, 0x8000, 0x8000, 0x30},
    {0x1090, 0x1070, 0x81, 0x151, 0x592, 0x282, 0x632, 0x4c2, 0x172, 0x4f2, 0x113, 0x134, 0x824, 0x8000, 0x8000, 0x8000, 0x8000, 0x8000, 0x8000, 0x8000, 0x8000, 0x8000, 0x8000, 0x30},
    {0x1098, 0x1078, 0x89, 0x159, 0x59a, 0x28a, 0x63a, 0x4ca, 0x17a, 0x4fa, 0x11b, 0x13c, 0x82c, 0x8000, 0x8000, 0x8000, 0x8000, 0x8000, 0x8000, 0x8000, 0x8000, 0x8000, 0x8000, 0x30},
    {0x11b0, 0x8c0, 0x31, 0xf1, 0xa2, 0x3b2, 0x322, 0x42, 0xe2, 0x2d2, 0x143, 0x1d3, 0x2954, 0x8000, 0x8000, 0x8000, 0x8000, 0x8000, 0x8000, 0x8000, 0x8000, 0x8000, 0x8000, 0x30},
    {0x11b8, 0x8c8, 0x39, 0xf9, 0xaa, 0x3ba, 0x32a, 0x4a, 0xea, 0x2da, 0x14b, 0x1db, 0x29d4, 0x8000, 0x8000, 0x8000, 0x8000, 0x8000, 0x8000, 0x8000, 0x8000, 0x8000, 0x8000, 0x30},
    {0x1110, 0x9d0, 0x41, 0x312, 0x102, 0x382, 0x6c2, 0x402, 0x652, 0x1f2, 0x83, 0x53, 0x8a4, 0x8000, 0x8000, 0x8000, 0x8000, 0x8000, 0x8000, 0x8000, 0x8000, 0x8000, 0x8000, 0x30},
    {0x1118, 0x9d8, 0x49, 0x31a, 0x10a, 0x38a, 0x6ca, 0x40a, 0x65a, 0x1fa, 0x8b, 0x5b, 0x8ac, 0x8000, 0x8000, 0x8000, 0x8000, 0x8000, 0x8000, 0x8000, 0x8000, 0x8000, 0x8000, 0x30},
    {0x140, 0x11e0, 0x181, 0xc1, 0x292, 0x502, 0x5a2, 0x442, 0x372, 0x93, 0x104, 0x14, 0x295c, 0x8000, 0x8000, 0x8000, 0x8000, 0x8000, 0x8000, 0x8000, 0x8000, 0x8000, 0x8000, 0x40},
    {0x148, 0x11e8, 0x189, 0xc9, 0x29a, 0x50a, 0x5aa, 0x44a, 0x37a, 0x9b, 0x10c, 0x1c, 0x29dc, 0x8000, 0x8000, 0x8000, 0x8000, 0x8000, 0x8000, 0x8000, 0x8000, 0x8000, 0x8000, 0x40},
    {0x1000, 0x10f0, 0xa1, 0x1d1, 0x112, 0x122, 0x532, 0x5c2, 0x2c2, 0x562, 0x193, 0x1f3, 0x173, 0x285c, 0x8000, 0x8000, 0x8000, 0x8000, 0x8000, 0x8000, 0x8000, 0x8000, 0x8000, 0x40},
    {0x1008, 0x10f8, 0xa9, 0x1d9, 0x11a, 0x12a, 0x53a, 0x5ca, 0x2ca, 0x56a, 0x19b, 0x1fb, 0x17b, 0x28dc, 0x8000, 0x8000, 0x8000, 0x8000, 0x8000, 0x8000, 0x8000, 0x8000, 0x8000, 0x40},
};
struct Tile { int valid, ty, mt, nt, flush, nkb, wide; };
__device__ __forceinline__ Tile decode(int v) {
  Tile t;
  t.valid = v < 0x8000; t.ty = v & 7; t.mt = (v >> 3) & 15; t.nt = (v >> 7) & 15; t.flush = (v >> 11) & 3; t.wide = v & 0x2000;
  t.nkb = t.ty == T_W4 ? 56 : (t.ty == T_WO ? 64 : 16);
  return t;
}
__device__ __forceinline__ unsigned ld_acq(int c) {
  unsigned v;
  asm volatile("ld.acquire.gpu.global.u32 %0, [%1];" : "=r"(v) : "l"(g_cnt + c * 8) : "memory");
  return v;
}
__device__ __forceinline__ void wait_cnt(int c, unsigned target) {
  unsigned v;
  int n = 0;
#pragma unroll 1
  do {
    v = ld_acq(c);
    if (v >= target) break;
    __nanosleep(NSLP);
  } while (++n < WAIT_LIM);
}
__device__ __forceinline__ void sig_cnt(int c, int v = 1) {
  asm volatile("red.release.gpu.global.add.u32 [%0], %1;" ::"l"(g_cnt + c * 8), "r"(v) : "memory");
}
__device__ __forceinline__ void fence_async_all() { asm volatile("fence.proxy.async.global;" ::: "memory"); }
__device__ __forceinline__ void arrive_both(uint32_t bar) {
  asm volatile(
      "{.reg .b32 r0, r1; mapa.shared::cluster.u32 r0, %0, 0; mapa.shared::cluster.u32 r1, %0, 1;\n"
      "mbarrier.arrive.shared::cluster.b64 _, [r0];\n"
      "mbarrier.arrive.shared::cluster.b64 _, [r1];}" ::"r"(bar) : "memory");
}
__device__ __forceinline__ void load_b(uint32_t dst, const CUtensorMap* m, int k, int ng, uint32_t bar) {
  asm volatile(
      "cp.async.bulk.tensor.3d.shared::cluster.global.mbarrier::complete_tx::bytes.multicast::cluster [%0], [%1, {%3, %4, %5}], [%2], %6;"
      ::"r"(dst), "l"(m), "r"(bar), "r"(0), "r"(k), "r"(ng), "h"((uint16_t)3) : "memory");
}
__device__ __forceinline__ float gelu_f(float x) {
  float u = x * (0.7978845608f + 0.0356774081f * x * x), t;
  asm("tanh.approx.f32 %0, %1;" : "=f"(t) : "f"(u));
  return fmaf(x, t, x);
}
__device__ __forceinline__ float silu_f(float x) {
  float hx = 0.5f * x, t;
  asm("tanh.approx.f32 %0, %1;" : "=f"(t) : "f"(hx));
  return fmaf(hx, t, hx);
}

__device__ __forceinline__ uint32_t add2(uint32_t a, uint32_t b) { uint32_t r; asm("add.rn.bf16x2 %0, %1, %2;" : "=r"(r) : "r"(a), "r"(b)); return r; }
__device__ __forceinline__ uint32_t mul2(uint32_t a, uint32_t b) { uint32_t r; asm("mul.rn.bf16x2 %0, %1, %2;" : "=r"(r) : "r"(a), "r"(b)); return r; }
__device__ __forceinline__ uint32_t fma2(uint32_t a, uint32_t b, uint32_t c) { uint32_t r; asm("fma.rn.bf16x2 %0, %1, %2, %3;" : "=r"(r) : "r"(a), "r"(b), "r"(c)); return r; }

__device__ __forceinline__ uint32_t scale2(uint32_t d, uint32_t hi, uint32_t lo) {
  uint32_t r;
  asm("fma.rn.bf16x2 %0, %1, %2, %3;" : "=r"(r) : "r"(d), "r"(hi), "r"(mul2(d, lo)));
  return r;
}
__device__ __forceinline__ void split2(float s, uint32_t& hi, uint32_t& lo) {
  hi = pack_bf16(s, s);
  const float r = s - bf_lo(hi);
  lo = pack_bf16(r, r);
}
__device__ __forceinline__ float ln_inv(float m2) {
  float sd, inv;
  asm("sqrt.approx.f32 %0, %1;" : "=f"(sd) : "f"(rbf(rbf(m2 * (1.f / 1024.f)) + 1e-5f)));
  asm("rcp.approx.f32 %0, %1;" : "=f"(inv) : "f"(rbf(sd)));
  return inv;
}
__device__ __forceinline__ void ln_packed(uint32_t* u) {
  float s = 0.f, s2 = 0.f;
#pragma unroll
  for (int i = 0; i < 16; i++) { s += bf_lo(u[i]); s2 += bf_hi(u[i]); }
  s += s2;
#pragma unroll
  for (int o = 16; o > 0; o >>= 1) s += __shfl_xor_sync(~0u, s, o);
  float mean = s * (1.f / 1024.f), q = 0.f, q2 = 0.f;
#pragma unroll
  for (int i = 0; i < 16; i++) { float a = bf_lo(u[i]) - mean, b = bf_hi(u[i]) - mean; q = fmaf(a, a, q); q2 = fmaf(b, b, q2); }
  q += q2;
#pragma unroll
  for (int o = 16; o > 0; o >>= 1) q += __shfl_xor_sync(~0u, q, o);
  const uint32_t nmb = pack_bf16(-mean, -mean);
  uint32_t hi, lo;
  split2(ln_inv(q), hi, lo);
#pragma unroll
  for (int i = 0; i < 16; i++) u[i] = scale2(add2(u[i], nmb), hi, lo);
}
__device__ __forceinline__ void row_ld(uint32_t* u, const bf16* p, int lane) {
#pragma unroll
  for (int i = 0; i < 4; i++) {
    uint4 v = __ldcg((const uint4*)(p + i * 256 + lane * 8));
    u[i * 4] = v.x; u[i * 4 + 1] = v.y; u[i * 4 + 2] = v.z; u[i * 4 + 3] = v.w;
  }
}
__device__ __forceinline__ void row_st(const uint32_t* u, bf16* p, int lane) {
#pragma unroll
  for (int i = 0; i < 4; i++) *(uint4*)(p + i * 256 + lane * 8) = make_uint4(u[i * 4], u[i * 4 + 1], u[i * 4 + 2], u[i * 4 + 3]);
}

template <int N>
__device__ __forceinline__ void activate(uint32_t* pk, int act) {
  if (act == T_W1 || act == T_W3) {
#pragma unroll
    for (int i = 0; i < N; i++) pk[i] = pack_bf16(gelu_f(bf_lo(pk[i])), gelu_f(bf_hi(pk[i])));
  } else if (act == T_W4) {
#pragma unroll
    for (int i = 0; i < N; i++) pk[i] = pack_bf16(silu_f(bf_lo(pk[i])), silu_f(bf_hi(pk[i])));
  }
}
__device__ __forceinline__ void epi_store(const uint32_t* pk, uint32_t bf, uint32_t xo, const CUtensorMap* cm, int col, int row, int lane) {
  if (lane == 0) asm volatile("cp.async.bulk.wait_group.read 1;" ::: "memory");
  __syncwarp();
#pragma unroll
  for (int q = 0; q < 4; q++) stsm4(bf + (xo ^ (q << 5)), pk[q * 4], pk[q * 4 + 1], pk[q * 4 + 2], pk[q * 4 + 3]);
  fence_async_smem();
  __syncwarp();
  if (lane == 0) {
    tma_store_2d(cm, bf, col, row);
    asm volatile("cp.async.bulk.commit_group;" ::: "memory");
  }
}

#define DP0 3
#define DPK 4
#define DPS 1
#define NA0 5
#define NA1 11
#define PP 3
#define DQ 2
constexpr int NRD = 5, D_STAGES = 5, D_W = 0, D_RING = 2 * (8 - NRD) * 16384, D_SUM = D_RING + 5 * 16384;
static_assert(D_SUM + 16384 <= G_STG, "smem");
__device__ constexpr int d_head(int i) { return i < DQ ? i : (i < DQ + 8 - NRD ? i + NRD - DQ : i - 8 + NRD); }

__global__ void __cluster_dims__(2, 1, 1) __launch_bounds__(384, 1)
k_gemm(const __grid_constant__ GemmMaps maps, const bf16* __restrict__ x, bf16* __restrict__ out) {
  extern __shared__ __align__(1024) unsigned char smem_raw[];
  const uint32_t sb = smem_u32(smem_raw);
  const int tid = threadIdx.x, wid = __shfl_sync(~0u, tid >> 5, 0), wg = wid >> 2, w = wid & 3, lane = tid & 31;
  const int rank = blockIdx.x & 1, cl = blockIdx.x >> 1;
  const uint32_t bFull = sb + G_BAR, bEmpty = bFull + 32, bPub = bFull + 64, dFull = bFull + 72, dEmpty = dFull + 48, dW = dEmpty + 48, dReady = dW + 8,
                 xF = bFull + 256, xE = xF + 64;
  const int dq = blockIdx.x & 3;
  if (tid >= 32 && tid < 32 + 21) asm volatile("prefetch.tensormap [%0];" ::"l"(&maps.a[0] + (tid - 32)) : "memory");
  if (tid == 0) {
    TG(95, 0);
    if (sb & 1023) __trap();
    for (int i = 0; i < G_STAGES; i++) { mbar_init(bFull + i * 8, 1); mbar_init(bEmpty + i * 8, 4); }
    for (int i = 0; i < D_STAGES; i++) { mbar_init(dFull + i * 8, 1); mbar_init(dEmpty + i * 8, 2); }
    for (int i = 0; i < 16; i++) mbar_init(xF + i * 8, 1);
    mbar_init(dW, 1);
    mbar_init(bPub, 8);
    sts_u1(dReady, 0);
    asm volatile("fence.mbarrier_init.release.cluster;" ::: "memory");
  }
  __syncthreads();
  asm volatile("barrier.cluster.arrive.relaxed.aligned;" ::: "memory");
  if (wg == 2) {
    asm volatile("setmaxnreg.dec.sync.aligned.u32 40;");
    asm volatile("barrier.cluster.wait.aligned;" ::: "memory");
    if (w == 0 && lane == 0) {
      int st = 0, ph = 1, pe = 0, pcol = 0, pmt = 0;
#define ELOAD(j)                                                                           \
  {                                                                                        \
    mbar_wait(bEmpty + st * 8, ph);                                                        \
    const uint32_t full = bFull + st * 8, sa = sb + st * G_STAGE_BYTES;                    \
    mbar_expect_tx(full, (pe - 2) * 16384);                                                \
    tma_load_2d(sa, &maps.e[pe * 2 - 5], pcol + (j) * 64, pmt * 128, full);                \
    if (pe == T_WO) tma_load_2d(sa + 16384, &maps.e[2], pcol + (j) * 64, pmt * 128, full); \
    if (++st == G_STAGES) { st = 0; ph ^= 1; }                                             \
  }
      for (int r = 0;; r++) {
        const Tile t = decode(c_list[blockIdx.x][r]);
        if (!t.valid) break;
        const int mt = t.mt;
        const CUtensorMap *am = &maps.a[t.ty], *bm = am + 5;
        if (r == 0) {
          for (int kb = 0; kb < G_STAGES; kb++) {
            mbar_expect_tx(bFull + kb * 8, G_STAGE_BYTES);
            load_b(sb + kb * G_STAGE_BYTES + 16384 + rank * 16384, bm, kb * 64, t.nt * 4 + rank * 2, bFull + kb * 8);
          }
        }
        if (t.ty == T_W1) wait_cnt(C_LN, 96);
        else if (t.ty == T_W2) { wait_cnt(C_H1 + mt, 4); if (mt > 0) wait_cnt(C_H1 + mt - 1, 4); if (mt < 15) wait_cnt(C_H1 + mt + 1, 4); }
        else if (t.ty == T_W3) wait_cnt(C_LN1 + mt, 4);
        else if (t.ty == T_W4) wait_cnt(C_H3 + mt, 14);
        else wait_cnt(C_OX + mt * 4 + 3, 128);
        fence_async_all();
        TG(r, 0);
        if (r == 0 && cl == 0) ST(5);
        for (int kb = 0; kb < t.nkb; kb++) {
          const bool early = r == 0 && kb < G_STAGES;
          if (pe && !(kb & ~12)) ELOAD(kb >> 2);
          if (kb == 56) { wait_cnt(C_G + mt, 4); fence_async_all(); }
          if ((kb & 52) == 48) tma_prefetch_2d(am + (t.ty + 17 - (kb >> 3)), t.nt * 256 + (kb & 3) * 64, mt * 128);
          mbar_wait(bEmpty + st * 8, ph);
          const uint32_t full = bFull + st * 8, sa = sb + st * G_STAGE_BYTES;
          if (!early) mbar_expect_tx(full, G_STAGE_BYTES);
          int roff = 0;
          if (t.ty == T_W2) { int gq = kb >> 2; roff = (gq & 1) ? (gq >> 1) + 1 : -((gq >> 1) + 1); }
          tma_load_2d(sa, am, kb * 64, mt * 128 + roff, full);
          if (t.wide) { tma_load_3d(sa + 16384, bm, 0, kb * 64, t.nt * 4, full); tma_load_3d(sa + 32768, bm, 0, kb * 64, t.nt * 4 + 2, full); }
          else if (!early) load_b(sa + 16384 + rank * 16384, bm, kb * 64, t.nt * 4 + rank * 2, full);
          if (++st == G_STAGES) { st = 0; ph ^= 1; }
        }
        pe = t.ty >= T_W4 ? t.ty : 0; pcol = t.nt * 256; pmt = mt;
        if (pe && t.flush) {
          for (int j = 0; j < 4; j++) ELOAD(j);
          pe = 0;
        }
        for (int i = 0; i < (t.ty == T_W2 ? 2 : 0); i++) {
          mbar_wait(bEmpty + st * 8, ph);
          const uint32_t full = bFull + st * 8, sa = sb + st * G_STAGE_BYTES;
          mbar_expect_tx(full, 32768);
          tma_load_2d(sa, &maps.e[0], pcol + i * 128, mt * 128, full);
          tma_load_2d(sa + 16384, &maps.e[0], pcol + i * 128 + 64, mt * 128, full);
          if (++st == G_STAGES) { st = 0; ph ^= 1; }
        }
      }
      if (c_list[blockIdx.x][23] < NSEG) {
        mbar_expect_tx(dW, D_RING);
        for (int i = 0; i < G_STAGES; i++) {
          mbar_wait(bEmpty + st * 8, ph);
          for (int b = st * 3; b < min(st * 3 + 3, 11); b++) {
            const uint32_t bar = b < 6 ? dW : dFull + (b - 6) * 8;
            if (b > 5) mbar_expect_tx(bar, 16384);
            tma_load_3d(sb + b * 16384, &maps.b[T_WO], 0, dq * 1024 + (b < 5 ? b + 5 : b == 5 ? 15 : b - 6) * 64, cl & ~1, bar);
          }
          if (++st == G_STAGES) { st = 0; ph ^= 1; }
        }
      }
    } else if (w == 3 && lane == 0) {
      int ph = 0;
      for (int r = 0;; r++) {
        const Tile t = decode(c_list[blockIdx.x][r]);
        if (!t.valid) break;
        if (t.ty != T_WO) { mbar_wait_long(bPub, ph); ph ^= 1; sig_cnt(t.ty * 16 + t.mt); TG(r, 3); }
      }
    }
    __syncwarp();
    if (w < 3) bar_sync(3, 96);
    const int s0 = c_list[blockIdx.x][23];
    if (!(w & 1) && lane == 0 && s0 < NSEG) {
      int st = w >> 1, ph = 0, ready = s0;
      for (int n = st; n < 4 * (NSEG - s0); n += 2) {
        const int s = s0 + (n >> 3) * 2 + 1;
        if (s >= ready) {
#pragma unroll 1
          for (int it = 0; s >= ready && it < 64 * WAIT_LIM; it++)
            asm volatile("ld.acquire.cta.shared.u32 %0, [%1];" : "=r"(ready) : "r"(dReady) : "memory");
          fence_async_all();
          TG(24 + s, 0);
        }
        mbar_wait(dEmpty + st * 8, ph);
        const uint32_t full = dFull + st * 8, sa = sb + D_RING + st * 16384;
        if ((s | 2) == 51) TG(40 + (n & 7), s & 2);
        mbar_expect_tx(full, 16384);
        tma_load_3d(sa, &maps.od, 0, s * 32 - 32, dq * 16 + d_head(n & 7) * 2, full);
        if (n == 1) {
          mbar_expect_tx(dW, 5 * 16384);
          for (int q = 0; q < 5; q++) tma_load_3d(sb + D_W + q * 16384, &maps.b[T_WO], 0, dq * 1024 + NRD * 128 + q * 64, cl & ~1, dW);
        }
        if ((st += 2) >= D_STAGES) { st -= D_STAGES; ph ^= 1; }
      }
    } else if (w == 1) {
      int ready = s0;
#pragma unroll 1
      for (int it = 0; ready < NSEG; it++) {
        const int q = min(ready + (lane & 7), NSEG - 1);
        const bool ok = (lane < 16 && ld_acq(lane < 8 ? C_OX + q : C_G + (q >> 2)) >= (lane < 8 ? 128 : 4)) || it > WAIT_LIM;
        const uint32_t m = __ballot_sync(~0u, ok);
        const int n = __ffs(~(m & (m >> 8) & 255)) - 1;
        ready = min(ready + n, NSEG);
        __syncwarp();
        if (n == 0) __nanosleep(NSLP);
        else if (lane == 0) asm volatile("st.release.cta.shared.u32 [%0], %1;" ::"r"(dReady), "r"(ready) : "memory");
      }
      uint32_t last = 0;
      if (lane == 0) asm volatile("atom.acq_rel.gpu.global.inc.u32 %0, [%1], %2;" : "=r"(last) : "l"(g_cnt + C_DONE * 8), "r"(gridDim.x - 1) : "memory");
      if (__shfl_sync(~0u, last, 0) == gridDim.x - 1)
        for (int i = lane; i < C_DONE; i += 32) g_cnt[i * 8] = 0;
    }
    __syncwarp();
  } else {
    asm volatile("setmaxnreg.inc.sync.aligned.u32 232;");
    asm volatile("barrier.cluster.wait.aligned;" ::: "memory");
    const bool leader = (tid & 127) == 0;
    bool pubq = false;
    {
      const int rr = (lane & 7) + ((lane >> 3) & 1) * 8;
      const uint32_t sb = __shfl_sync(~0u, smem_u32(smem_raw), 0), bFull = sb + G_BAR, bEmpty = bFull + 32, bPub = bFull + 64;
      const uint32_t xo = __shfl_sync(~0u, rr * 128 + (((lane >> 4) ^ (rr & 7)) << 4), lane), buf = sb + G_STG + wid * 4096, erow = wid * 2048;
      int st = 0, ph = 0, r = 0, tv = c_list[blockIdx.x][0];
      uint32_t pk[64];
      int dact = -1, ecol = 0, drow = 0, done = 0, prev = 0;
      bool hold = false, flush = false, fast = false;
      const CUtensorMap* dcm = nullptr;
      float acc[128];
      if (PP && wg) bar_arrive(4, 256);
      while (true) {
        const Tile t = decode(tv);
        const int mt = t.mt;
        const bool run = t.valid && !hold;
#define KBLOCK(kb)                                                                                      \
  {                                                                                                     \
    mbar_wait(bFull + st * 8, ph);                                                                      \
    uint32_t sa = sb + st * G_STAGE_BYTES;                                                              \
    uint64_t da = make_desc(sa + wg * 8192, 16, 1024, 1), db = make_desc(sa + 16384, 8192, 1024, 1);    \
    if (PP) bar_sync(4 + wg, 256);                                                                      \
    WG_FENCE();                                                                                         \
    _Pragma("unroll") for (int k = 0; k < 4; k++) {                                                     \
      wgmma_n256(acc, da + k * 2, db + k * 128, ((kb) | k) != 0);                                       \
      if (k == PP - 1) bar_arrive(5 - wg, 256);                                                         \
    }                                                                                                   \
    WG_COMMIT();                                                                                        \
    if ((kb) > 0) { WG_WAIT(1); if (leader) arrive_both(bEmpty + prev * 8); }                           \
    prev = st;                                                                                          \
    if (++st == G_STAGES) { st = 0; ph ^= 1; }                                                          \
  }
#define PUBLISH()                                                                                       \
  {                                                                                                     \
    if (lane == 0) { asm volatile("cp.async.bulk.wait_group 0;" ::: "memory"); if (pubq) mbar_arrive(bPub); } \
    __syncwarp();                                                                                       \
    pubq = false;                                                                                       \
  }
#define EAPPLY(p, eb, OP)                                                                  \
  _Pragma("unroll") for (int q = 0; q < 4; q++) {                                          \
    uint32_t a[4];                                                                         \
    ldsm4(a, (eb) + (xo ^ (q << 5)));                                                      \
    _Pragma("unroll") for (int i = 0; i < 4; i++) (p)[q * 4 + i] = OP((p)[q * 4 + i], a[i]); \
  }
#define ADDH(a, b) fma2(a, dact == T_WO ? 0x3F803F80u : 0x3F003F00u, b)
        const bool eop = dact == T_W4 || dact == T_WO;
        const bool slow = run && !fast;
#pragma unroll
        for (int c = 0; c < 4; c++) {
          const int es = st, eph = ph;
          if (eop && ++st == G_STAGES) { st = 0; ph ^= 1; }
          if (run) KBLOCK(c ? c : done);
          if (run && c == 0 && tid == 0 && !done) TG(r, 1);
          if (eop) {
            mbar_wait(bFull + es * 8, eph);
            const uint32_t eb = sb + es * G_STAGE_BYTES + erow;
            if (dact == T_WO) EAPPLY(pk + c * 16, eb + 16384, mul2);
            EAPPLY(pk + c * 16, eb, ADDH);
            bar_sync(1 + wg, 128);
            if (leader) arrive_both(bEmpty + es * 8);
          }
          activate<NA0>(pk + c * 16, dact);
          if (slow) KBLOCK(1);
          activate<NA1 - NA0>(pk + c * 16 + NA0, dact);
          if (run) KBLOCK(1);
          activate<16 - NA1>(pk + c * 16 + NA1, dact);
          if (slow) KBLOCK(1);
          if (c == 0 && pubq) PUBLISH();
          if (dact >= 0) epi_store(pk + c * 16, buf + (c & 1) * 2048, xo, dcm, ecol + c * 64, drow, lane);
        }
        if (run) done += slow ? 16 : 8;
        if (dact == T_W2) {
          const uint2* sp = g_rstat + (drow + (lane >> 2)) * 4 + (lane & 3);
          uint2 q[2];
          for (int n = 0; n < WAIT_LIM; n++) {
            q[0] = ld_rlx2(sp); q[1] = ld_rlx2(sp + 32);
            if (!__any_sync(~0u, q[0].y == 0u || q[1].y == 0u)) break;
          }
          uint32_t nmb[2], hi[2], lo[2];
#pragma unroll
          for (int e = 0; e < 2; e++) {
            const float sp = __uint_as_float(q[e].x);
            float a = sp + __shfl_xor_sync(~0u, sp, 1);
            a += __shfl_xor_sync(~0u, a, 2);
            const float mean = a * (1.f / 1024.f), dm = sp * (1.f / 256.f) - mean;
            float v = fmaf(256.f * dm, dm, __uint_as_float(q[e].y & 0x7fffffffu));
            v += __shfl_xor_sync(~0u, v, 1);
            v += __shfl_xor_sync(~0u, v, 2);
            nmb[e] = pack_bf16(-mean, -mean);
            split2(ln_inv(v), hi[e], lo[e]);
          }
#pragma unroll
          for (int i = 0; i < 64; i++) pk[i] = scale2(add2(pk[i], nmb[i & 1]), hi[i & 1], lo[i & 1]);
          dact = T_LN;
          dcm = &maps.c[5];
          hold = flush;
          continue;
        }
        pubq = dact >= 0 && dact != T_WO;
        dact = -1;
        if (!run) {
          WG_WAIT(0);
          if (!t.valid) break;
          PUBLISH();
          hold = false;
          continue;
        }
        uint2* sp = g_rstat + (mt * 128 + wid * 16 + (lane >> 2)) * 4 + t.nt;
        if (t.ty == T_W4 && (lane & 3) == 0) { st_rlx2(sp, 0, 0); st_rlx2(sp + 32, 0, 0); }
        dact = t.ty; ecol = t.nt * 256; drow = mt * 128 + wid * 16; dcm = &maps.c[t.ty];
        flush = t.flush & 1; fast = t.flush || t.ty == T_W2; hold = flush || (t.flush && t.ty == T_W2);
        tv = c_list[blockIdx.x][++r];
#pragma unroll 1
        for (int kb = done; kb < t.nkb; kb++) {
          KBLOCK(1);
          if (kb == done + 1 && pubq) PUBLISH();
        }
        WG_WAIT(0);
        if (leader) arrive_both(bEmpty + prev * 8);
        if (tid == 0) TG(r - 1, 2);
#pragma unroll
        for (int i = 0; i < 64; i++) pk[i] = pack_bf16(acc[2 * i], acc[2 * i + 1]);
        done = 0;
        if (dact == T_W2) {
#pragma unroll
          for (int h = 0; h < 2; h++) {
            mbar_wait(bFull + st * 8, ph);
            const uint32_t eb = sb + st * G_STAGE_BYTES + erow;
            EAPPLY(pk + h * 32, eb, ADDH);
            EAPPLY(pk + h * 32 + 16, eb + 16384, ADDH);
            bar_sync(1 + wg, 128);
            if (leader) arrive_both(bEmpty + st * 8);
            if (++st == G_STAGES) { st = 0; ph ^= 1; }
          }
          const uint32_t one = 0x3F803F80u;
          float *sm = acc, *s2 = acc + 4, *q0 = acc + 8, *q1 = acc + 12;
#pragma unroll
          for (int i = 0; i < 32; i++) acc[i] = 0.f;
#pragma unroll
          for (int i = 0; i < 64; i += 4) mma16816((i & 4) ? s2 : sm, pk[i], pk[i + 1], pk[i + 2], pk[i + 3], one, one);
          sm[0] += s2[0]; sm[2] += s2[2];
          const uint32_t c0 = pack_bf16(sm[0] * (-1.f / 256.f), sm[0] * (-1.f / 256.f)), c1 = pack_bf16(sm[2] * (-1.f / 256.f), sm[2] * (-1.f / 256.f));
#pragma unroll
          for (int i = 0; i < 64; i += 4) {
            const uint32_t a0 = add2(pk[i], c0), a1 = add2(pk[i + 1], c1), a2 = add2(pk[i + 2], c0), a3 = add2(pk[i + 3], c1);
            mma16816(q0, a0, a1, a2, a3, a0, a2);
            mma16816(q1, a0, a1, a2, a3, a1, a3);
          }
          if ((lane >> 3) == (lane & 3)) {
            const float e0 = fmaf(sm[0], 1.f / 256.f, bf_lo(c0)), e1 = fmaf(sm[2], 1.f / 256.f, bf_lo(c1));
            const float m0 = fmaxf(fmaf(-256.f * e0, e0, (lane & 4) ? q0[1] : q0[0]), 0.f);
            const float m1 = fmaxf(fmaf(-256.f * e1, e1, (lane & 4) ? q1[3] : q1[2]), 0.f);
            st_rlx2(sp, __float_as_uint(sm[0]), __float_as_uint(m0) | 0x80000000u);
            st_rlx2(sp + 32, __float_as_uint(sm[2]), __float_as_uint(m1) | 0x80000000u);
          }
          __syncwarp();
        }
      }
    }
    if (tid == 0) { TG(95, 1); ST(8 + cl); }
    const int s0 = c_list[blockIdx.x][23];
    if (s0 < NSEG) {
      uint32_t W[NRD * 8][4];
      const uint32_t peer = peer_base(sb, rank ^ 1);
#define XFREE() if (lane == 0) { mbar_expect_tx(xF + wid * 8, 2048); arrive_remote(xE + wid * 8 + peer); }
      int st = 0, ph = 0;
      const uint32_t xw = sb + D_RING + wg * 8192 + ((lane >> 4) * 8 + (lane & 7)) * 128 + (((w * 2 + ((lane >> 3) & 1)) ^ (lane & 7)) << 4);
      mbar_wait(dW, 0);
#pragma unroll
      for (int k = 0; k < 20; k++) ldsm4t(W[20 + k], xw - D_RING + (k >> 2) * 16384 + (k & 3) * 2048);
#pragma unroll
      for (int i = 0; i < D_STAGES; i++) {
        mbar_wait(dFull + st * 8, ph);
#pragma unroll
        for (int k = 0; k < 4; k++) ldsm4t(W[i * 4 + k], xw + st * 16384 + k * 2048);
        bar_sync(1 + wg, 128);
        if (leader) mbar_arrive(dEmpty + st * 8);
        if (++st == D_STAGES) { st = 0; ph ^= 1; }
      }
      PUBLISH();
      XFREE();
      if (tid == 0) TG(95, 2);
      const uint32_t in = sb + G_STG + wid * 4096 + lane * 16, mine = (cl & 1) * 1024, keep = D_SUM - G_STG - wid * 2048;
      uint32_t dA = (uint32_t)make_desc(sb + D_W + wg * 8192, 1024, 1024, 1);
      const uint32_t dB = (uint32_t)make_desc(sb + D_RING, 16, 1024, 1);
      const uint32_t eb = (dq * 16 + (lane >> 2)) * D_ + (cl >> 1) * 128 + wid * 16 + (lane & 3) * 2, xb = blockIdx.x * 8192 + tid;
      int pend = 0, fin = 0;
#define SUM_LD(j) { a = lds_f4(in + (mine ^ (1024 - ((j) >> 1) * 1024)) + ((j) & 1) * 512); b = lds_f4(in + (mine ^ (1024 - ((j) >> 1) * 1024)) + ((j) & 1) * 512 + 2048); }
#define SUM_ST(j, on, u)                                                                                    \
  {                                                                                                      \
    const float c[4] = {a.x + b.x, a.y + b.y, a.z + b.z, a.w + b.w};                                     \
    if ((j) < 2)                                                                                         \
      asm volatile("{.reg .pred p; .reg .b128 r; setp.ne.b32 p, %5, 0; mov.b128 r, {%1,%2,%3,%4}; @p st.relaxed.gpu.global.b128 [%0], r;}" \
                   ::"l"(g_dx + (xb ^ 16384) + ((u) & 31) * 256 + (j) * 256), "r"(nz(asu(c[0]))), "r"(asu(c[1])), "r"(asu(c[2])), "r"(asu(c[3])), "r"(on) : "memory"); \
    else if (on) sts_f4(in + keep + ((u) & 2) * 512 + ((j) & 1) * 512, c);                                                 \
  }
#define OPERANDS(t, e)                                                                                   \
  {                                                                                                      \
    e[0] = ld_rlx1(g_gate + eo + t * 8 * D_); e[1] = ld_rlx1(g_gate + eo + t * 8 * D_ + 8);              \
    e[2] = __ldg((const uint32_t*)(x + eo + t * 8 * D_)); e[3] = __ldg((const uint32_t*)(x + eo + t * 8 * D_ + 8)); \
  }
#define RECV() { r = ld_rlx4(g_dx + xo); q = ld_rlx4(g_dx + xo + 256); }
#define CHECK() { for (int n = 0; (r.x == 0u || q.x == 0u) && n < WAIT_LIM; n++) RECV(); __syncwarp(); }
#define FIN_LD(on)                                                                                       \
  {                                                                                                      \
    if (on) { st_rlx4(g_dx + xo, 0, 0, 0, 0); st_rlx4(g_dx + xo + 256, 0, 0, 0, 0); }                    \
    a = lds_f4(in + keep + (u & 2) * 512); b = lds_f4(in + keep + (u & 2) * 512 + 512);                                                  \
  }
#define FIN_T(r, a)                                                                                      \
  {                                                                                                      \
    r.x = pack_bf16(a.x + asf(r.x), a.y + asf(r.y)); r.y = pack_bf16(a.z + asf(r.z), a.w + asf(r.w));    \
    asm volatile("movmatrix.sync.aligned.m8n8.trans.b16 %0, %0;" : "+r"(r.x));                           \
    asm volatile("movmatrix.sync.aligned.m8n8.trans.b16 %0, %0;" : "+r"(r.y));                           \
  }
#define FIN_ST(t, e, r, on)                                                                              \
  {                                                                                                      \
    const uint32_t y = add2(mul2(r.x, e[0]), e[2]), z = add2(mul2(r.y, e[1]), e[3]);                     \
    if (on) asm volatile("st.global.b32 [%0+%3], %1; st.global.b32 [%0+%4], %2;" ::"l"(out + eo), "r"(y), "r"(z), "n"(t * 16 * D_), "n"(t * 16 * D_ + 16) : "memory"); \
  }
#pragma unroll 1
      for (int s = s0; s < NSEG; s += 2) {
        float d[32];
        uint32_t e[4], f[4];
        uint4 r, q;
        float4 a, b;
        int prev = 0;
        const uint32_t par = (s >> 1) & 1;
        int u = s - 2 - 2 * pend;
#define eo (eb + u * 32 * D_)
#define xo (xb + (u & 31) * 256)
#pragma unroll
        for (int i = 0; i < 8; i++) {
          if (i == DQ) mbar_wait(dW, 1);
          mbar_wait(dFull + st * 8, ph);
          if (leader && (s | 2) == 50) TG(24 + wg * 8 + i, s & 2);
          const uint32_t db = dB + st * 1024;
          asm volatile("" : "+r"(dA));
          WG_FENCE();
#pragma unroll
          for (int k = 0; k < 8; k++) {
            const int h = d_head(i), bo = (k >> 2) * 512 + (k & 3) * 2;
            if (h < NRD) wgmma_rs64(d, W[h < NRD ? h * 8 + k : 0], DSC(db + bo), (i | k) != 0);
            else wgmma_ss64(d, DSC(dA + ((h - NRD) * 2 + (k >> 2)) * 1024 + (k & 3) * 128), DSC(db + bo));
            if (i == DPS && !(k & 1)) { if (k) SUM_ST(k / 2 - 1, pend, s - 2); SUM_LD(k / 2); }
            if (i == DP0) { if (k == 0) OPERANDS(0, e); if (k == 2) OPERANDS(1, f); if (k == DPK) RECV(); }
            if (i == 7) {
              if (k == 0) FIN_LD(fin);
              if (k == 2) { FIN_T(r, a); FIN_T(q, b); }
              if (k == 4) FIN_ST(0, e, r, fin);
              if (k == 5) FIN_ST(1, f, q, fin);
            }
          }
          WG_COMMIT();
          if (leader && (s | 2) == 50) TG(24 + wg * 8 + i, 1 + (s & 2));
          if (i == DPS) { SUM_ST(3, pend, s - 2); if (pend) XFREE(); }
          if (i > 0) { WG_WAIT(1); if (leader) mbar_arrive(dEmpty + prev * 8); }
          if (i == DPS - 1 && pend) mbar_wait(xF + wid * 8, par ^ 1);
          if (i == 6 && fin) CHECK();
          if (i == 2) asm volatile("prefetch.global.L2 [%0];" ::"l"(((lane & 1) ? x : g_gate) + eb + (s * 32 + (lane & 2) * 4) * D_));
          prev = st;
          if (++st == D_STAGES) { st = 0; ph ^= 1; }
        }
        fin = pend;
        asm volatile("{.reg .pred p, g; ld.volatile.shared.u32 %0, [%1]; setp.gt.s32 p, %0, %2; setp.eq.b32 g, %3, 0;\n"
                     "@g barrier.red.and.aligned.pred p, 1, 128, p; @!g barrier.red.and.aligned.pred p, 2, 128, p; selp.b32 %0, 1, 0, p;}"
                     : "=&r"(pend) : "r"(dReady), "r"(s + 3), "r"(wg) : "memory");
        mbar_wait(xE + wid * 8, par);
        WG_WAIT(0);
        asm volatile("" : D16(d));
        asm volatile("" : D16((d + 16)));
        if (leader) mbar_arrive(dEmpty + prev * 8);
#pragma unroll
        for (int j = 0; j < 8; j++) {
          const uint32_t a = in + (j >> 2) * 1024 + ((j) & 1) * 512;
          if ((((j) >> 1) & 1) == rank) sts_f4(a, d + 4 * j);
          else sta4(a + 2048 + peer, make_uint4(asu(d[4 * j]), asu(d[4 * j + 1]), asu(d[4 * j + 2]), asu(d[4 * j + 3])), xF + wid * 8 + peer);
        }
        if (tid == 0) TG(24 + s, 1);
        if (!pend) {
          u = s - 2 * fin;
          OPERANDS(0, e);
          OPERANDS(1, f);
          RECV();
          mbar_wait(xF + wid * 8, par);
#pragma unroll
          for (int j = 0; j < 4; j++) { SUM_LD(j); SUM_ST(j, 1, s); }
          if (s + 2 < NSEG) XFREE();
#pragma unroll 1
          while (u < s || s + 2 == NSEG) {
            CHECK();
            FIN_LD(true);
            FIN_T(r, a);
            FIN_T(q, b);
            FIN_ST(0, e, r, true);
            FIN_ST(1, f, q, true);
            if (u == s || s + 2 < NSEG) break;
            u = s;
            OPERANDS(0, e);
            OPERANDS(1, f);
            RECV();
          }
          fin = 1;
        }
      }
    }
    else PUBLISH();
    if (PP && !wg) bar_sync(4, 256);
#undef eo
#undef xo
    if (tid == 0) { TG(95, 3); ST(32 + cl); }
  }
  asm volatile("barrier.cluster.arrive.relaxed.aligned; barrier.cluster.wait.aligned;" ::: "memory");
}
struct RecMaps { CUtensorMap w[3], wb[3], wo, xn, xn1, xn2, ox; };
#define NR1 13
#define NLOW 5
constexpr int R_WS = 0, R_WO = 2 * (32 - NR1) * 2048, R_Q = R_WO + 81920, R_K = R_Q + 6144, R_G1 = R_K + 6144,
              R_XN = R_WO + 98304, R_MEM = R_XN + 16384, R_VX = R_MEM + 16384, R_VM = R_VX + 8192, R_O = R_VM + 4096,
              R_TS = R_O + 4096, R_SC = R_TS + 5120, R_BAR = R_SC + 1280, R_TAB = R_BAR + 256, R_SMEM = R_TAB + 128;
constexpr int STG = R_SC - 2 * (32 + NR1) * 2048, NDIR = STG / 2048;
__device__ constexpr int stg(int g, int i) { return STG + (i == 0 ? 131072 + g * NR1 * 2048 : (i == 1 ? g * 98304 : 32768 + g * 32768)); }
static_assert(R_SMEM <= 232448 && R_G1 + 2048 <= R_XN && STG % 1024 == 0 && R_WO <= STG + 32768 && R_XN >= STG + 98304, "smem");
constexpr uint32_t SB = 1024;
constexpr int POLL_LIM = 1 << 20;
enum { BAR_MEM = 1, BAR_RED, BAR_O, BAR_BG, BAR_C, BAR_G1, BAR_X, BAR_H, BAR_ST };
#define bC (sb + R_BAR)
#define bX (bC + 48)
#define bWS (bC + 128)
#define bWo (bC + 136)
#define bM (bC + 144)
#define bS (bC + 152)
#define bTs (bC + 176)
#define bIn (bC + 184)
#define bTok (bC + 192)
#define aInfo (bC + 200)
#define aCal (bC + 224)
constexpr int XC_G2N = 256, XC_PRB = 384, XC_T = 386;
#define TINIT 6200, 1050, 200, 300, 400
__constant__ int c_tune[16] = {TINIT};
#define T_STEP c_tune[0]
#define T_G2 c_tune[1]
#define D_G1 c_tune[2]
#define D_G2 c_tune[3]
#define T_REL c_tune[4]
#define NWF 2
#define NBF 2
#define NCH 1
#define PAT 1
#define INSM(k) ((k) % 5 % 2 == 0)
#define SIDX(k) ((k) / 5 * 3 + ((k) % 5 + 1) / 2)
#define RIDX(k) (INSM(k) ? 0 : (k) - SIDX(k))
#define NEA0 3
#define NEA1 3
#define NEB 2
#define HOLE0 6
#define HOLE1 6
#define GST 0
#define THR 0
#define LEAD 15
#define WOT 2
#define WOW 1
#define XPOS 0
#define NPRB 3
#define PFX 2

__device__ __forceinline__ void xn_pair(const CUtensorMap* m, uint32_t dst, uint32_t bar, int bytes, int n, int c, int half) {
  mbar_expect_tx(bar, bytes);
  asm volatile(
      "cp.async.bulk.tensor.4d.shared::cluster.global.mbarrier::complete_tx::bytes [%0], [%1, {%3, %4, %5, %6}], [%2];"
      ::"r"(dst), "l"(m), "r"(bar), "r"(0), "r"(n * 32), "r"(c), "r"(half) : "memory");
}

__global__ void __launch_bounds__(384, 1)
k_rec(const __grid_constant__ RecMaps maps, const bf16* __restrict__ x, const bf16* __restrict__ mem0, unsigned char* xch) {
  extern __shared__ __align__(1024) unsigned char smem_raw[];
  const uint32_t sb = smem_u32(smem_raw);
  if ((sb & 0xffffff) != SB) __trap();
  const int tid = threadIdx.x, wid = __shfl_sync(~0u, tid >> 5, 0), wg = wid >> 2, w = wid & 3;
  const int lane = tid & 31;
  const int cta = blockIdx.x, h = cta / 3, j = cta - h * 3, cl = h >> 1, r0 = (h & 1) * 3;
  const bool isA = j < 2;
  if (tid >= 32 && tid < 32 + 11) asm volatile("prefetch.tensormap [%0];" ::"l"(&maps.w[0] + (tid - 32)) : "memory");
  if (tid == 0 && cta == 0) ST(2);
  asm volatile("griddepcontrol.launch_dependents;" ::: "memory");
  uint32_t u[3][16] = {};
  const int row = min((cta * 8 + wid) * 3, S_ - 3);
  if (wg < 2) {
#pragma unroll
    for (int i = 0; i < 3; i++) row_ld(u[i], x + (size_t)(row + i) * D_, lane);
  }
  if (tid == 0) {
    for (int i = 0; i < 18; i++) mbar_init(bC + i * 8, 1);
    mbar_init(bM, 2); mbar_init(bS, 1); mbar_init(bTs, 1); mbar_init(bIn, 2); mbar_init(bTok, 4);
    asm volatile("fence.mbarrier_init.release.cluster;" ::: "memory");
  }
  if ((wid >> 1) != 4) {
    bar_sync(BAR_G1, 384);
#pragma unroll 1
    for (int pass = wg >> 1; pass < 2; pass++) {
      bf16* dst = (pass ? g_xn2 : g_xn) + (size_t)row * D_;
      if (pass == 0) {
        if (__any_sync(~0u, after(c_tune[15], u[0][15] ^ u[1][15] ^ u[2][15], c_tune[15]))) __trap();
        bar_arrive(BAR_X, 320);
        if (tid == 0) TG(1, 0);
      }
#pragma unroll
      for (int i = 0; i < 3; i++) ln_packed(u[i]);
      if (wg < 2 && (cta * 8 + wid) * 3 < S_) {
#pragma unroll
        for (int i = 0; i < 3; i++) row_st(u[i], dst + i * D_, lane);
      }
    }
  } else {
    bar_arrive(BAR_G1, 384);
    uint4* z = (uint4*)(xch + (isA ? (h * 2 + j) * 4 : XC_G2N + ((h >> 3) & 1) * 48 + (h >> 4) * 64 + ((h >> 1) & 3) * 4 + (h & 1)) * 4096);
#pragma unroll 4
    for (int i = 0; i < (isA ? 16 : 4); i++) z[i * 64 + (tid & 63)] = make_uint4(0, 0, 0, 0);
    if (cta == cl * 6) {
      uint32_t* p = (uint32_t*)(xch + (XC_PRB + w) * 4096 + cl * 128);
      st_rlx1(p + lane, 0);
      uint32_t lat = ~0u;
#pragma unroll 1
      for (int r = 0; r < NPRB && lane == 0; r++) {
        uint32_t v, c0 = clk32();
        asm volatile("atom.relaxed.gpu.global.add.u32 %0, [%1], 1;" : "=r"(v) : "l"(p) : "memory");
        if (v >> 30) break;
        lat = min(lat, clk32() - c0);
      }
      if (lane == 0) { sts_u1(aInfo + w * 4, lat); TG(3, w); }
      __syncwarp();
    }
  }
  asm volatile("barrier.cluster.arrive.relaxed.aligned;" ::: "memory");
#define WMAP(g) (&maps.w[isA ? (g) : 2])
#define WCOL(g) (h * 128 + (isA ? j : (g)) * 64)
  const uint32_t xlo = (uint32_t)(uint64_t)xch, xhi = (uint32_t)((uint64_t)xch >> 32);
#define XP(off) xptr(xlo + (off), xhi)
  if (wg < 2) {
    fence_async_all();
    if (tid == 0) TG(1, 1);
    if (wid != 7) bar_arrive(BAR_C, 256);
    else bar_sync(BAR_C, 256);
    if (tid == 224) { sig_cnt(C_LN); TG(0, 1); }
    __syncwarp();
    if (wid == 7) bar_arrive(BAR_BG, 96);
    asm volatile("setmaxnreg.inc.sync.aligned.u32 224;");
    const uint32_t l16c = opaque(sb + lane * 16);
    const uint32_t xwc = opaque(sb + ((lane >> 4) * 8 + (lane & 7)) * 128 + (((w * 2 + ((lane >> 3) & 1)) ^ (lane & 7)) << 4));
    uint32_t W0[32][4], W1[NR1][4];
#pragma unroll
    for (int i = 0; i < 3; i++) {
      mbar_wait(bC + (wg * 3 + i) * 8, 0);
      if (i == 0 && tid == 0) TG(1, 2);
#pragma unroll
      for (int k = 0; k < (i ? 16 : NR1); k++) ldsm4t(i ? W0[i ? i * 16 - 16 + k : 0] : W1[i ? 0 : k], (wg ? stg(1, i) : stg(0, i)) + k * 2048 + xwc);
      if (i) bar_arrive(i == 1 ? BAR_ST : BAR_H, 288);
    }
    if (tid == 0) TG(1, 3);
    asm volatile("barrier.cluster.wait.aligned;" ::: "memory");
    mbar_wait(bWS, 0);
    if (tid == 0) TG(0, 2);
    const uint32_t dX = (uint32_t)make_desc(SB + R_XN, 16, 1024, 1) + wg * 512, dW = (uint32_t)make_desc(SB + R_WS, 1024, 1024, 1) + wg * (32 - NR1) * 128;
    const uint32_t pB = peer_base(sb, r0 + 2);
#pragma unroll 1
    for (int s = 0; s < NSEG; s++) {
      uint32_t xw = xwc, l16 = l16c;
      asm volatile("" : "+r"(xw), "+r"(l16));
#define LANE0 ((l16 & 511) == 0)
      {
        float d0[16], d1[16];
#pragma unroll
        for (int c = 0; c < 8; c++) {
          if (c == 7 || !(c & 1)) mbar_wait(bX + (c < 4 ? c / 2 : (c == 7 ? 6 : c - 2) + wg) * 8, s & 1);
          if (c == NEB && s > 0 && !isA && wid == 7) {
            bar_sync(BAR_ST, 160);
            if (LANE0 && s > 1) sig_cnt(C_OX + s - 2, 4);
            __syncwarp();
          }
          if (c <= 3 && s > 0 && c == (isA ? (wg ? NEA1 : NEA0) : NEB)) bar_sync(BAR_BG, 384);
          if ((c == HOLE0 || c == HOLE1) && s > 0 && isA && c == (wg ? HOLE1 : HOLE0)) bar_sync(BAR_H, 384);
          const uint32_t db = dX + (c & 2) * 512 + (c & 1) * 256 + (c < 4 ? 0 : c_tune[15]);
          uint32_t tmp[4];
          if (c < NLOW) {
#pragma unroll
            for (int i = 0; i < 4; i++) asm volatile("or.b32 %0, %1, %2;" : "=r"(tmp[i]) : "r"(W0[c * 4][i]), "r"(c_tune[15]));
          }
          WG_FENCE();
#pragma unroll
          for (int kk = 0; kk < 4; kk++) {
            const int k = c * 4 + kk;
            if (c < 7) wgmma_rs32(d0, kk == 0 && c < NLOW ? tmp : W0[k], DSC(db + kk * 2), k != 0);
            if (kk == 0 && c + 1 < NLOW) WG_COMMIT();
            if (!INSM(k)) wgmma_rs32(d1, W1[RIDX(k)], DSC(db + kk * 2), k != 0);
            else wgmma_ss32(d1, DSC(dW + SIDX(k) * 128), DSC(db + kk * 2), k != 0);
          }
          WG_COMMIT();
          if (c == 7) {
#pragma unroll
            for (int kk = 0; kk < 4; kk++) wgmma_rs32(d0, W0[28 + kk], DSC(db + kk * 2), 1);
            WG_COMMIT();
          }
          const bool pause = c + 1 == (isA ? (wg ? NEA1 : NEA0) : NEB);
          if ((c == 1 || c == 2) && pause) WG_WAIT(0);
          if (c + 1 < NLOW || c == 4) WG_WAIT(1);
#pragma unroll
          for (int f = 1; f <= 3; f++) {
            if (f != c && f + 1 != c) continue;
            const bool early = f < 3 && f + 1 == (isA ? (wg ? NEA1 : NEA0) : NEB);
            if (w == 0 && LANE0 && early == (f == c)) {
              if (f == 1) {
                xn_pair(&maps.xn1, sb + R_XN + wg * 8192, bX + (2 + wg) * 8, 8192, s, 4, wg);
              } else {
                mbar_expect_tx(bX + (f * 2 + wg) * 8, 4096);
                tma_load_2d(sb + R_MEM + wg * 8192 + (f - 2) * 4096, &maps.xn, wg * 512 + (f + 4) * 64, s * 32, bX + (f * 2 + wg) * 8);
              }
            }
            __syncwarp();
          }
        }
        const uint32_t ex = l16 + R_XN + w * 2048;
        WG_WAIT(1);
        asm volatile("" : D16(d1));
#pragma unroll
        for (int i = 0; i < 4; i++) sts_f4(ex + wg * 8192 + i * 512, d1 + 4 * i);
        bar_sync(BAR_C, 256);
#pragma unroll
        for (int i = 0; i < 4; i++) {
          const float4 x = lds_f4(ex + (wg ^ 1) * 8192 + i * 512);
          d1[4 * i] = x.x; d1[4 * i + 1] = x.y; d1[4 * i + 2] = x.z; d1[4 * i + 3] = x.w;
        }
        WG_WAIT(0);
        asm volatile("" : D16(d0));
        if (w == 0 && LANE0) mbar_arrive(bM);
        if (s > 0 && tid < 32) { s--; TR(17); s++; }
        uint32_t f[8];
#pragma unroll
        for (int i = 0; i < 8; i++) f[i] = pack_bf16(d0[2 * i] + d1[2 * i], d0[2 * i + 1] + d1[2 * i + 1]);
        if (isA) {
          const uint32_t aq = l16 + (l16 & 256) * 3 + R_Q + wg * 6144 + w * 256;
          stsm4t(aq, f[0], f[1], f[2], f[3]);
          stsm4t(aq + 2048, f[4], f[5], f[6], f[7]);
        } else {
          const uint32_t av = l16 + R_VX + w * 2048 + wg * 1024;
          if (s > 0) mbar_wait(bTok, (s - 1) & 1);
          sts_u4(av, make_uint4(f[0], f[1], f[2], f[3])); sts_u4(av + 512, make_uint4(f[4], f[5], f[6], f[7]));
        }
        if (s > 0 && tid < 32) { s--; TR(18); s++; }
      }
      {
        const uint32_t aW = xw + R_WS + wg * (32 - NR1) * 2048, aMem = l16 + R_MEM + wg * 8192;
        float a[4][4];
        uint32_t b[16][4], f[32 - NR1][4], ck[14];
#define PAIR(i) (i)
#pragma unroll
        for (int i = 0; i < NWF; i++) ldsm4t(f[i], aW + i * 2048);
#pragma unroll
        for (int i = 0; i < 4; i++) a[i][0] = a[i][1] = a[i][2] = a[i][3] = 0.f;
        bar_sync(BAR_MEM, 384);
#pragma unroll
        for (int i = 0; i < NBF - 1; i++) ldsm4t(b[i], aMem + PAIR(i) * 512);
#pragma unroll
        for (int i = 0; i < 16; i++) {
          const int p = PAIR(i);
          if (i + NBF - 1 < 16) ldsm4t(b[i + NBF - 1], aMem + PAIR(i + NBF - 1) * 512);
#pragma unroll
          for (int e = 0; e < 2; e++) {
            const int k = 2 * PAIR(i > 0 ? i - 1 : 0) + e, q = SIDX(k) + NWF;
            if (i > 0 && INSM(k) && q < 32 - NR1) ldsm4t(f[q], aW + q * 2048);
          }
          if (i < 14) ck[i] = clk32();
          if (i == 1 && tid < 32) TRX(0, ck[0]);
          if (i > 1) ck[0] |= ck[i - 2];
#pragma unroll
          for (int e = 0; e < 2; e++) {
            const int k = 2 * p + e;
            const uint32_t* u = INSM(k) ? f[INSM(k) ? SIDX(k) : 0] : W1[RIDX(k)];
            mma16816(a[2 + e % NCH], u[0], u[1], u[2], u[3], b[i][2 * e], b[i][2 * e + 1]);
            mma16816(a[e % NCH], W0[k][0], W0[k][1], W0[k][2], W0[k][3], b[i][2 * e], b[i][2 * e + 1]);
          }
        }
        l16 = after(l16, ck[0], 0);
        if (NCH == 2) {
#pragma unroll
          for (int i = 0; i < 4; i++) { a[0][i] += a[1][i]; a[2][i] += a[3][i]; }
        }
        const uint4 r = make_uint4(pack_bf16(a[0][0], a[0][1]), pack_bf16(a[0][2], a[0][3]), pack_bf16(a[2][0], a[2][1]), pack_bf16(a[2][2], a[2][3]));
        if (!isA) {
          sts_u4(l16 + R_VM + wid * 512, r);
          bar_arrive(BAR_RED, 384);
          if (tid < 32) TR(1);
          if (tid == 160) TRCAL(s);
          __syncwarp();
          continue;
        }
        stsm4t((l16 & ~256u) + (((l16 >> 8) & 1) ^ wg) * 6144 + R_Q + 4096 + wg * 1024 + w * 256, r.x, r.y, r.z, r.w);
        bar_arrive(BAR_RED, 384);
        fence_async_smem();
        bar_sync(BAR_X, 352);
        if (tid < 32) TR(1);
        if (tid == 160) TRCAL(s);
        __syncwarp();
      }
      if (wg == 0) {
        float c[24];
        WG_FENCE();
#pragma unroll
        for (int i = 0; i < 4; i++) wgmma_ss48(c, make_desc(SB + R_Q + i * 256, 128, 1024, 0), make_desc(SB + R_K + i * 256, 128, 1024, 0), i != 0);
        WG_COMMIT();
        asm volatile("" : "+r"(l16));
        const uint32_t at = l16 + R_TS + w * 2560 + j * 640 + pB, au = at + 512 - (l16 & 511) / 4 * 3;
        mbar_wait(bIn, s & 1);
        WG_WAIT(0);
        asm volatile("" : D16(c), "+f"(c[16]), "+f"(c[17]), "+f"(c[18]), "+f"(c[19]), "+f"(c[20]), "+f"(c[21]), "+f"(c[22]), "+f"(c[23]));
        if (w < 2) {
#pragma unroll
          for (int r = 0; r < 2; r++) {
            const float* e = c + 2 * r;
            sta4(at + r * 1280, make_uint4(pack_bf16(e[0], e[1]), pack_bf16(e[4], e[5]), pack_bf16(e[8], e[9]), pack_bf16(e[12], e[13])), bTs + pB);
            sta1(au + r * 1280, pack_bf16(e[16] + e[20], e[17] + e[21]), bTs + pB);
          }
        }
        if (tid < 32) TR(14);
      }
    }
  } else {
    asm volatile("setmaxnreg.dec.sync.aligned.u32 56;");
    const int at = tid & 127, red = h * 2 + j;
    const int g = w & 1, slot = g * (32 - NR1) + SIDX(lane);
    if (w >= 2) {
      const bool lead = cl == LEAD;
      if (lead) bar_arrive(BAR_X, 320);
      else bar_sync(BAR_X, 320);
      if (lane < 3) mbar_expect_tx(bC + (g * 3 + lane) * 8, lane ? 32768 : NR1 * 2048);
      if (lane == 3 && g) mbar_expect_tx(bWS, R_WO);
      if (!INSM(lane)) tma_load_2d_ef(sb + stg(0, 0) + (g * NR1 + RIDX(lane)) * 2048, WMAP(g ^ 1), WCOL(g ^ 1), g * 512 + lane * 16, bC + g * 24);
      __syncwarp();
#pragma unroll 1
      for (int i = 0; i < 3; i++) {
        if (i == (lead ? 2 : XPOS)) bar_sync(BAR_BG, 96);
        if (i >= THR && !lead) mbar_wait(bC + (g * 3 + i - THR) * 8, 0);
        if (lane == 0 && i < 2) tma_load_2d_ef(sb + STG + (i ? g + 1 : g * 3) * 32768, WMAP(g) + 3, WCOL(g), g * 512 + i * 256, bC + (g * 3 + 1 + i) * 8);
        __syncwarp();
      }
      if (INSM(lane) && slot < NDIR) tma_load_2d_ef(sb + R_WS + slot * 2048, WMAP(g ^ 1), WCOL(g ^ 1), g * 512 + lane * 16, bWS);
      __syncwarp();
    }
    if (w == 3) {
      bar_sync(BAR_ST, 288);
      fence_async_smem();
      if (INSM(lane) && slot >= NDIR) tma_load_2d_ef(sb + R_WS + slot * 2048, WMAP(0), WCOL(0), 512 + lane * 16, bWS);
      __syncwarp();
      if (lane < 2) {
        wait_cnt(C_LN, gridDim.x);
        fence_async_all();
        xn_pair(&maps.xn2, sb + R_XN + lane * 16384, bX + lane * 8, 16384, 0, lane * 2, 0);
        TG(2, 1);
      }
      __syncwarp();
    }
    if (w < 2) bar_sync(BAR_RED, 64);
    if (at == 0) {
      uint32_t v = 1;
      if (cta == cl * 6) v += ((__popc((XC_PRB + (lds_u1(aInfo + 4) < lds_u1(aInfo))) & 0xb3) & 1) << cl) << 16;
      asm volatile("red.release.gpu.global.add.u32 [%0], %1;" ::"l"(g_cnt + C_CHK * 8), "r"(v) : "memory");
      int n = 0;
#pragma unroll 1
      do {
        asm volatile("ld.acquire.gpu.global.u32 %0, [%1];" : "=r"(v) : "l"(g_cnt + C_CHK * 8) : "memory");
      } while ((v & 0xffff) < gridDim.x && ++n < WAIT_LIM);
      sts_u1(aInfo + 8, v >> 16);
      TG(2, 0);
    }
    bar_sync(BAR_O, 128);
    const uint32_t pmask = __shfl_sync(~0u, lds_u1(aInfo + 8), 0), myp = (pmask >> cl) & 1;
    const int nt = isA ? 5 : 6;
    uint32_t mytile = 0;
    {
      int n = 0;
      for (int far = 1; far >= 0; far--)
        for (int i = 0; i < nt; i++) {
          const int T = j * 5 + i, p = (pmask >> T) & 1;
          if ((p ^ myp) != far) continue;
          if (n == lane) {
            mytile = T;
            sts_u1(sb + R_TAB + w * 32 + n * 4, xlo + xchunk((T * 4 + w) * 4 + (h >> 4) * 2, p) + (h & 15) * 256);
          }
          n++;
        }
    }
    if (w == 3) {
      bar_sync(BAR_H, 288);
      fence_async_smem();
      if (WOW) mbar_wait(bWS, 0);
#pragma unroll 1
      for (int i = 0; i < nt; i++) {
        if (i >= WOT) mbar_wait(bC + (i - WOT) * 8, 1);
        const bool tail = i >= nt - WOT;
        if (lane == i) {
          if (!tail || i == nt - 1) mbar_expect_tx(tail ? bWo : bC + i * 8, tail ? WOT * 16384 : 16384);
          tma_load_2d(sb + R_WO + i * 16384, &maps.wo, mytile * 64, h * 128, tail ? bWo : bC + i * 8);
        }
        __syncwarp();
      }
    }
    asm volatile("barrier.cluster.wait.aligned;" ::: "memory");
    {
      uint4 v[8];
#pragma unroll
      for (int i = 0; i < 8; i++) v[i] = __ldg((const uint4*)(mem0 + (lane >> 2) * D_ + w * 256 + i * 32 + (lane & 3) * 8));
      mbar_wait(bM, 0);
#pragma unroll
      for (int i = 0; i < 8; i++)
        stsm4t(sb + R_MEM + w * 4096 + i * 512 + (lane & 6) * 64 + (lane >> 3) * 32 + (lane & 1) * 16, v[i].x, v[i].y, v[i].z, v[i].w);
    }
    if (at == 96) { const uint2 e = timer_edge(); sts_u2(aCal, e.x, e.y); }
    int lim = POLL_LIM;
    const uint32_t l8c = opaque(lane * 8);
    const uint32_t pA = peer_base(sb, r0), pB = peer_base(sb, r0 + 2 - (j >> 1));
    const uint32_t uR = xchunk(red * 4 + (w & 2), myp) + (w & 1) * 2048;
    const uint32_t uW = xchunk(XC_G2N + (red >> 4) * 4, (myp ^ w ^ 1) & 1) + (red & 15) * 256;
    const uint32_t uG = xchunk(XC_G2N, myp) + w * 512;
    const uint64_t dWo = make_desc(SB + R_WO, 1024, 1024, 1), dO = make_desc(SB + R_O, 128, 128, 0);
#pragma unroll 1
    for (int s = 0; s < NSEG; s++) {
      const uint32_t tag = (s & 1) ^ 1, par = s & 1;
      const bool more = s + 1 < NSEG;
      uint32_t l8 = l8c;
      asm volatile("" : "+r"(l8));
#define STORE_OX(n, w) do {                                                                 \
          tma_store_2d(&maps.ox, sb + R_O + (w) * 1024, h * 128 + (w) * 16, (n) * 32);         \
          tma_store_2d(&maps.ox, sb + R_TS + (w) * 1280, h * 128 + 64 + (w) * 16, (n) * 32); } while (0)
      bar_sync(BAR_MEM, 384);
      if (w == 3) {
        if (l8 == 0) {
          const uint32_t ta = ld_rlx1(XP(XC_T << 12));
          if (more) {
            fence_async_smem();
            xn_pair(&maps.xn2, sb + R_XN, bX, 16384, s + 1, 0, 0);
            mbar_expect_tx(bS, isA ? 2048 : 1280);
          }
          if (!isA) mbar_expect_tx(bTs, 5120);
          const uint4 o = lds_u4(aCal);
          const uint2 e = timer_edge();
          float f = (float)(e.y - o.y) * rcp((float)(e.x - o.x));
          if (s > 1) f = 0.75f * asf(o.z) + 0.25f * f;
          uint32_t d = (int)((float)(int)(ta - e.x) * f);
          if (d > 8192) d = 0;
          sts_u4(aCal, make_uint4(e.x, e.y, asu(f), ta));
#pragma unroll
          for (int i = 0; i < 4; i++) sts_u1(sb + R_TAB + i * 32 + 24, e.y + d);
        }
        if (s + PFX < NSEG && l8 < 128)
          asm volatile("prefetch.global.L2 [%0];" ::"l"(g_xn + (size_t)(s + PFX) * 32 * D_ + (cta & 31) * 1024 + l8 * 8));
      }
#define XN23() do { if (w == 3 && l8 == 0 && more) { fence_async_smem(); xn_pair(&maps.xn2, sb + R_MEM, bX + 8, 16384, s + 1, 2, 0); } __syncwarp(); } while (0)
      if (s == 0 && at == 0) TG(2, 3);
      if (s == 0) mbar_wait(bWo, 0);
      if (s == 0 && at == 0) TG(2, 2);
      if (isA && more && w < 3) {
        uint32_t k[4][4], q[4][4];
        uint32_t ak = sb + R_K + w * 2048 + l8 * 2 + (l8 & 128) * 6, aq = sb + R_Q + 4096 + (l8 & 63) * 2 + (l8 & 64) * 16 + (l8 & 128);
        asm volatile("" : "+r"(ak), "+r"(aq));
        if (w == 2) bar_sync(BAR_RED, 384);
#pragma unroll
        for (int i = 0; i < 4; i++) ldsm4(k[i], ak + i * 256);
        if (w != 2) bar_sync(BAR_RED, 384);
#pragma unroll
        for (int i = 0; i < 4; i++) ldsm4(q[i], aq + i * 256);
        float c[4][4];
#pragma unroll
        for (int i = 0; i < 4; i++) c[i][0] = c[i][1] = c[i][2] = c[i][3] = 0.f;
#pragma unroll
        for (int i = 0; i < 4; i++) {
          mma16816(c[i & 1], q[i][0], q[i][1], q[i][2], q[i][3], k[i][0], k[i][1]);
          mma16816(c[2 + (i & 1)], q[i][0], q[i][1], q[i][2], q[i][3], k[i][2], k[i][3]);
        }
        const float a0 = (c[0][0] + c[0][2]) + (c[1][0] + c[1][2]), a1 = (c[0][1] + c[0][3]) + (c[1][1] + c[1][3]);
        const float b0 = (c[2][0] + c[2][2]) + (c[3][0] + c[3][2]), b1 = (c[2][1] + c[2][3]) + (c[3][1] + c[3][3]);
        const uint32_t as = sb + R_SC + j * 640 + w * 256;
        if (w < 2) {
          const uint32_t x = pack_bf16(a0, a1), y = pack_bf16(b0, b1);
          sta2(as + l8 + pB, x, y, bS + pB);
        } else {
          const uint32_t x = pack_bf16(a0 + b0, a1 + b1);
          sta1(as + (l8 >> 1) + pB, x, bS + pB);
        }
        bar_arrive(BAR_X, 352);
        if (w == 0) TR(2);
      } else if (isA) {
        bar_sync(BAR_RED, 384);
        if (w < 3) bar_arrive(BAR_X, 352);
        XN23();
      } else {
        if (w < 2 && l8 == 0) {
          if (s > 0) {
            fence_async_smem();
            STORE_OX(s - 1, 2 * w); STORE_OX(s - 1, 2 * w + 1);
            asm volatile("cp.async.bulk.commit_group; cp.async.bulk.wait_group.read 0;" ::: "memory");
          }
          arrive_remote(bIn + pA); arrive_remote(bIn + pB);
          if (!more) { asm volatile("cp.async.bulk.wait_group 0;" ::: "memory"); sig_cnt(C_OX + s - 1, 2); }
        }
        __syncwarp();
        uint4 vx[4];
#pragma unroll
        for (int i = 0; i < 4; i++) vx[i] = lds_u4(sb + R_VX + (i & 1) * 1024 + (i >> 1) * 512 + w * 2048 + l8 * 2);
        bar_sync(BAR_RED, 384);
        XN23();
        if (more) {
          const uint32_t am = sb + R_VM + w * 512 + l8 * 2;
          const uint2 vm[4] = {lds_u2(am), lds_u2(am + 2056), lds_u2(am + 8), lds_u2(am + 2048)};
          mbar_wait(bS, par);
          if (w == 0) TR(4);
          float sc[10];
          const uint2 u0 = lds_u2(sb + R_SC + l8), u1 = lds_u2(sb + R_SC + 256 + l8), v0 = lds_u2(sb + R_SC + 640 + l8), v1 = lds_u2(sb + R_SC + 896 + l8);
          sum_scores(sc, u0, u1, lds_u1(sb + R_SC + 512 + (l8 >> 1)), v0, v1, lds_u1(sb + R_SC + 1152 + (l8 >> 1)));
          uint32_t p[5];
          softmax_e(sc);
#pragma unroll
          for (int i = 0; i < 5; i++) p[i] = pack_bf16(sc[2 * i], sc[2 * i + 1]);
          if (w == 0) TR(5);
          float o0[4], o1[4], sm[4];
          pv_mma(o0, o1, sm, vx, vm, p);
          const float i0 = rcp(sm[0]), i1 = rcp(sm[1]);
          const uint32_t aO = sb + R_O + w * 512 + (l8 >> 1);
          const uint32_t o[4] = {pack_bf16(o0[0] * i0, o0[1] * i1), pack_bf16(o0[2] * i0, o0[3] * i1), pack_bf16(o1[0] * i0, o1[1] * i1), pack_bf16(o1[2] * i0, o1[3] * i1)};
#pragma unroll
          for (int i = 0; i < 4; i++) { sta1(aO + i * 128 + pA, o[i], bS + pA); sta1(aO + i * 128 + pB, o[i], bS + pB); }
#pragma unroll
          for (int i = 0; i < 4; i++) sts_u1(aO + i * 128, o[i]);
          asm volatile("cp.async.bulk.wait_group 0;" ::: "memory");
        }
      }
      if (!more && isA) break;
      const uint32_t ts = sb + R_TS + w * 1280;
      uint4 tu, tv;
      uint32_t tu4, tv4, tp = 0;
#define LOAD_TS() tu = lds_u4(ts + l8 * 2); tv = lds_u4(ts + 640 + l8 * 2); tu4 = lds_u1(ts + 512 + (l8 >> 1)); tv4 = lds_u1(ts + 1152 + (l8 >> 1))
      if (!more) {
        mbar_wait(bTs, par);
        LOAD_TS();
      } else {
        float m[6][4];
        const uint4 ta = lds_u4(sb + R_TAB + w * 32);
        const uint4 tb = lds_u4(sb + R_TAB + w * 32 + 16);
        tp = tb.z;
        if (isA) mbar_wait(bS, par);
        else bar_sync(BAR_ST, 160);
        fence_async_smem();
        if (w == 0) TR(8);
        WG_FENCE();
#define WO_GROUP(t0, t1)                                                                                          \
  _Pragma("unroll") for (int kk = 0; kk < 8; kk++) _Pragma("unroll") for (int i = t0; i < t1; i++)                \
      wgmma_n8_tt(m[i], dWo + i * 1024 + kk * 128, dO + (kk & 3) * 32 + (kk >> 2) * 16, kk != 0);                 \
  WG_COMMIT();
        WO_GROUP(0, 3)
        if (isA) { wgmma_n8_tt(m[5], dWo, dO, 0); WO_GROUP(3, 5) } else { WO_GROUP(3, 6) }
#define G1_SEND(i, lo) st_rlx2(xptr(lo + l8, xhi), tagu(pack_bf16(m[i][0], m[i][1]), tag), pack_bf16(m[i][2], m[i][3]))
#define PIN4(i) asm volatile("" : "+f"(m[i][0]), "+f"(m[i][1]), "+f"(m[i][2]), "+f"(m[i][3]))
        WG_WAIT(1);
        PIN4(0); PIN4(1); PIN4(2);
        G1_SEND(0, ta.x); G1_SEND(1, ta.y); G1_SEND(2, ta.z);
        mbar_wait(isA ? bS : bTs, par);
        LOAD_TS();
        WG_WAIT(0);
        PIN4(3); PIN4(4); PIN4(5);
        bar_arrive(BAR_BG, 384);
        G1_SEND(3, ta.w); G1_SEND(4, tb.x);
        if (!isA) G1_SEND(5, tb.y);
        if (w == 0) TR(9);
      }
      const uint32_t slot = ((s & 1) * 48 + (s & 2) * 32) << 12;
      asm volatile("" : "+r"(l8));
      if (isA) {
        const unsigned char* pR = XP(uR + l8);
        unsigned char* pW = XP(((uW + slot) ^ ((w & 2) << 17)) + l8);
        uint32_t sel = (l8 >> 6) == ((l8 >> 3) & 3) ? (l8 & 32 ? 0x3F800000u : 0x3F80u) : 0;
        asm volatile("" : "+r"(sel), "+l"(pR), "+l"(pW));
        uint32_t ci = wait_clk(tp, D_G1), bad;
        if (w == 0) TRX(10, ci);
#pragma unroll 1
        do {
          uint2 p[8];
#pragma unroll
          for (int i = 0; i < 8; i++) p[i] = ld_rlx2(pR + i * 256);
          ci = clk32();
          float d[2][4] = {};
#pragma unroll
          for (int i = 0; i < 4; i++) mma16816(d[i & 1], p[2 * i].x, p[2 * i].y, p[2 * i + 1].x, p[2 * i + 1].y, sel, sel);
          bad = or3(ne2(p[0].x, p[1].x, tag), ne2(p[2].x, p[3].x, tag), ne2(p[4].x, p[5].x, tag)) | ne2(p[6].x, p[7].x, tag);
          sts_u2(sb + R_G1 + w * 512 + l8, asu(d[0][0] + d[1][0]), asu(d[0][1] + d[1][1]));
          sts_u2(sb + R_G1 + w * 512 + 256 + l8, asu(d[0][2] + d[1][2]), asu(d[0][3] + d[1][3]));
        } while (__any_sync(~0u, (bad & 1) && --lim > 0));
        bar_sync(BAR_G1, 128);
        if (w < 2) {
          const float4 a = lds_f4(sb + R_G1 + l8 * 2), b = lds_f4(sb + R_G1 + 512 + l8 * 2), c = lds_f4(sb + R_G1 + 1024 + l8 * 2), d = lds_f4(sb + R_G1 + 1536 + l8 * 2);
          st_rlx2(pW, nz(pack_bf16((a.x + b.x) + (c.x + d.x), (a.y + b.y) + (c.y + d.y))),
                  nz(pack_bf16((a.z + b.z) + (c.z + d.z), (a.w + b.w) + (c.w + d.w))));
        } else {
          st_rlx2(pW, 0, 0);
        }
        bar_arrive(BAR_H, 384);
        if (w == 0) TR(12);
        if (w == 0) TRX(11, ci);
        if (cta == 0 && w == 3) {
          const uint4 o = lds_u4(aCal);
          const bool late = (int)(ci - tp) > 200;
          st_rlx1(XP(XC_T << 12), (late ? o.x : o.w) + (int)((float)(int)(T_STEP + (late ? ci - o.y + T_REL : 0)) * rcp(asf(o.z))));
        }
      } else {
        const uint32_t av = sb + R_VX + w * 2048 + l8 * 2, am = sb + R_VM + w * 512 + l8 * 2;
        float sc[10];
        sum_scores(sc, make_uint2(tu.x, tu.y), make_uint2(tu.z, tu.w), tu4, make_uint2(tv.x, tv.y), make_uint2(tv.z, tv.w), tv4);
        uint4 x = lds_u4(av), y = lds_u4(av + 512);
        uint2 m0 = lds_u2(am), m1 = lds_u2(am + 2056);
        const int lim_k = w * 8 + (l8 >> 5) - ((l8 >> 2) & 6);
#pragma unroll
        for (int i = 0; i < 8; i++)
          if ((i >> 1) * 8 + (i & 1) > lim_k) sc[i] = -1.0e9f * 11.313708498984761f;
        softmax_e(sc);
        float sum = ((sc[0] + sc[1]) + (sc[2] + sc[3])) + ((sc[4] + sc[5]) + (sc[6] + sc[7])) + (sc[8] + sc[9]);
        sum += __shfl_xor_sync(~0u, sum, 1);
        sum += __shfl_xor_sync(~0u, sum, 2);
        const float inv = rcp(sum);
#pragma unroll
        for (int i = 0; i < 6; i++) sts_u1(ts + i * 128 + (l8 >> 1), pack_bf16(sc[i < 5 ? 2 * i : 8] * inv, sc[i < 5 ? 2 * i + 1 : 9] * inv));
        fence_async_smem();
        bar_sync(BAR_O, 128);
        const uint32_t ao = sb + (l8 & 128) * 2 + (l8 & 56) * 4 + (((l8 >> 2) ^ (l8 >> 1)) & 16);
#pragma unroll
        for (int t = 0; t < 2; t++) {
          const uint32_t a0[4] = {x.x, x.y, x.z, x.w}, a1[4] = {y.x, y.y, y.z, y.w}, a2[4] = {m0.x, m0.y, m1.x, m1.y};
          float d[16];
          WG_FENCE();
          wgmma_rs32(d, a0, make_desc(SB + R_TS, 128, 1280, 0), 0);
          wgmma_rs32(d, a1, make_desc(SB + R_TS + 256, 128, 1280, 0), 1);
          wgmma_rs32(d, a2, make_desc(SB + R_TS + 512, 128, 1280, 0), 1);
          WG_COMMIT();
          if (t == 0) { x = lds_u4(av + 1024); y = lds_u4(av + 1536); m0 = lds_u2(am + 8); m1 = lds_u2(am + 2048); }
          WG_WAIT(0);
          asm volatile("" : D16(d));
          if (t == 0) {
#define CPY(v) asm volatile("or.b32 %0, %0, %1;" : "+r"(v) : "r"(c_tune[15]))
            CPY(x.x); CPY(x.y); CPY(x.z); CPY(x.w); CPY(y.x); CPY(y.y); CPY(y.z); CPY(y.w); CPY(m0.x); CPY(m0.y); CPY(m1.x); CPY(m1.y);
            __syncwarp();
            if (l8 == 0) mbar_arrive(bTok);
          }
          stsm4t(ao + (t ? R_TS + w * 1280 : R_O + w * 1024), pack_bf16(d[0], d[1]), pack_bf16(d[2], d[3]), pack_bf16(d[4], d[5]), pack_bf16(d[6], d[7]));
          stsm4t(ao + (t ? R_TS + w * 1280 : R_O + w * 1024) + 512, pack_bf16(d[8], d[9]), pack_bf16(d[10], d[11]), pack_bf16(d[12], d[13]), pack_bf16(d[14], d[15]));
        }
        if (w == 0) TR(13);
        if (!more) {
          fence_async_smem();
          __syncwarp();
          if (l8 == 0) {
            STORE_OX(s, w);
            asm volatile("cp.async.bulk.commit_group; cp.async.bulk.wait_group 0;" ::: "memory");
            sig_cnt(C_OX + s);
            if (w == 0) TG(0, 3);
            if (cta == 2) ST(4);
          }
          break;
        }
      }
      {
        const unsigned char* src = XP(uG + slot + l8 * 2);
        const uint32_t dst = sb + R_MEM + w * 512 + l8 * 2;
        wait_clk(tp + T_G2, isA ? D_G2 : 0);
        if (w == 0) TR(16);
        uint4 p[8];
#pragma unroll
        for (int i = 0; i < 8; i++) p[i] = ld_rlx4(src + (i >> 1) * 16384 + (i & 1) * 2048);
        mbar_wait(bM, par ^ 1);
        uint32_t mn = ~0u, ck = 0;
#pragma unroll
        for (int i = 0; i < 8; i += 2) {
          mn = __vimin3_u32(mn, p[i].x, p[i + 1].x);
          asm volatile("" : "+r"(mn));
          sts_u4(dst + i * 2048, p[i]);
          sts_u4(dst + i * 2048 + 2048, p[i + 1]);
          mn = __vimin3_u32(mn, __vimin3_u32(p[i].y, p[i].z, p[i].w), __vimin3_u32(p[i + 1].y, p[i + 1].z, p[i + 1].w));
          asm volatile("" : "+r"(mn));
        }
        if (__builtin_expect(__any_sync(~0u, mn == 0u), 0)) {
#pragma unroll 1
          do {
#pragma unroll
            for (int i = 0; i < 8; i++) reld4(p[i], src + (i >> 1) * 16384 + (i & 1) * 2048, min4(p[i]));
            mn = ~0u;
#pragma unroll
            for (int i = 0; i < 8; i++) { sts_u4(dst + i * 2048, p[i]); mn = min(mn, min4(p[i])); }
          } while (__any_sync(~0u, mn == 0u && --lim > 0));
          lim = after(lim, ck, 0);
        }
        if (w == 0) TR(15);
      }
    }
  }
  asm volatile("barrier.cluster.arrive.relaxed.aligned; barrier.cluster.wait.aligned;" ::: "memory");
}

typedef CUresult (*EncodeFn)(CUtensorMap*, CUtensorMapDataType, cuuint32_t, void*, const cuuint64_t*, const cuuint64_t*,
                             const cuuint32_t*, const cuuint32_t*, CUtensorMapInterleave, CUtensorMapSwizzle,
                             CUtensorMapL2promotion, CUtensorMapFloatOOBfill);
static EncodeFn g_encode = nullptr;

#define PROMO CU_TENSOR_MAP_L2_PROMOTION_L2_256B
static void map2d(CUtensorMap* m, const void* p, uint64_t cols, uint64_t rows, uint32_t bc, uint32_t br,
                  CUtensorMapSwizzle sw) {
  cuuint64_t dims[2] = {cols, rows}, strides[1] = {cols * 2};
  cuuint32_t box[2] = {bc, br}, es[2] = {1, 1};
  g_encode(m, CU_TENSOR_MAP_DATA_TYPE_BFLOAT16, 2, (void*)p, dims, strides, box, es, CU_TENSOR_MAP_INTERLEAVE_NONE, sw,
           sw == CU_TENSOR_MAP_SWIZZLE_64B ? PROMO : CU_TENSOR_MAP_L2_PROMOTION_L2_256B, CU_TENSOR_MAP_FLOAT_OOB_FILL_NONE);
}
static void map_w(CUtensorMap* m, const void* p, uint64_t N, uint64_t K) {
  cuuint64_t dims[3] = {64, K, N / 64}, strides[2] = {N * 2, 128};
  cuuint32_t box[3] = {64, 64, 2}, es[3] = {1, 1, 1};
  g_encode(m, CU_TENSOR_MAP_DATA_TYPE_BFLOAT16, 3, (void*)p, dims, strides, box, es, CU_TENSOR_MAP_INTERLEAVE_NONE,
           CU_TENSOR_MAP_SWIZZLE_128B, CU_TENSOR_MAP_L2_PROMOTION_L2_256B, CU_TENSOR_MAP_FLOAT_OOB_FILL_NONE);
}
static void map_seg(CUtensorMap* m, const void* p, uint64_t K, uint64_t parts, uint32_t np, CUtensorMapL2promotion pr = CU_TENSOR_MAP_L2_PROMOTION_L2_256B) {
  cuuint64_t dims[4] = {64, S_, K / 64 / parts, parts}, strides[3] = {K * 2, 128, K * 2 / parts};
  cuuint32_t box[4] = {64, 32, 2, np}, es[4] = {1, 1, 1, 1};
  g_encode(m, CU_TENSOR_MAP_DATA_TYPE_BFLOAT16, 4, (void*)p, dims, strides, box, es, CU_TENSOR_MAP_INTERLEAVE_NONE,
           CU_TENSOR_MAP_SWIZZLE_128B, pr, CU_TENSOR_MAP_FLOAT_OOB_FILL_NONE);
}
template <typename T>
static void* sym(T& s) { void* p = nullptr; cudaGetSymbolAddress(&p, s); return p; }

static void map_a(CUtensorMap* m, const void* p, int K) { map2d(m, p, K, S_, 64, 128, CU_TENSOR_MAP_SWIZZLE_128B); }
static void map_c(CUtensorMap* m, const void* p, int N) { map2d(m, p, N, S_, 64, 16, CU_TENSOR_MAP_SWIZZLE_128B); }

extern "C" void kernel_launch(void* const* d_in, const int* in_sizes, int n_in, void* d_out, int out_size) {
  const bf16* x = (const bf16*)d_in[0];
  const bf16* mem0 = (const bf16*)d_in[1];
  const bf16* Wo = (const bf16*)d_in[5];
  const bf16* w1 = (const bf16*)d_in[8];
  const bf16* w2 = (const bf16*)d_in[9];
  const bf16* w3 = (const bf16*)d_in[10];
  const bf16* w4 = (const bf16*)d_in[11];
  if (!g_encode) {
    void* fn = nullptr;
    cudaDriverEntryPointQueryResult qr;
    cudaGetDriverEntryPoint("cuTensorMapEncodeTiled", &fn, cudaEnableDefault, &qr);
    g_encode = (EncodeFn)fn;
    cudaFuncSetAttribute(k_gemm, cudaFuncAttributeMaxDynamicSharedMemorySize, G_SMEM);
    cudaFuncSetAttribute(k_rec, cudaFuncAttributeMaxDynamicSharedMemorySize, R_SMEM);
  }
  const bf16 *xn = (bf16*)sym(g_xn), *xn2 = (bf16*)sym(g_xn2), *gate = (bf16*)sym(g_gate), *ox = (bf16*)sym(g_ox),
             *h1 = (bf16*)sym(g_h1), *x1 = (bf16*)sym(g_x1), *ln1 = (bf16*)sym(g_ln1), *h3 = (bf16*)sym(g_h3);
  GemmMaps gm;
  map_a(&gm.a[0], xn2, D_); map_a(&gm.a[1], h1, D_); map_a(&gm.a[2], ln1, D_); map_a(&gm.a[3], h3, F_); map_a(&gm.a[4], ox, 4096);
  map_w(&gm.b[0], w1, D_, D_); map_w(&gm.b[1], w2, D_, D_); map_w(&gm.b[2], w3, F_, D_); map_w(&gm.b[3], w4, D_, F_);
  map_w(&gm.b[4], Wo, D_, 4096);
  map_c(&gm.c[0], h1, D_); map_c(&gm.c[1], x1, D_); map_c(&gm.c[2], h3, F_); map_c(&gm.c[3], gate, D_); map_c(&gm.c[4], d_out, D_);
  map_c(&gm.c[5], ln1, D_);
  map_a(&gm.e[0], xn, D_); map_a(&gm.e[1], x1, D_); map_a(&gm.e[2], gate, D_); map_a(&gm.e[3], x, D_);
  map_w(&gm.od, ox, 4096, S_);
  RecMaps rm;
  for (int i = 0; i < 3; i++) {
    map2d(&rm.w[i], d_in[2 + i], 4096, D_, 64, 16, CU_TENSOR_MAP_SWIZZLE_128B);
    map2d(&rm.wb[i], d_in[2 + i], 4096, D_, 64, 256, CU_TENSOR_MAP_SWIZZLE_128B);
  }
  map2d(&rm.wo, Wo, D_, 4096, 64, 128, CU_TENSOR_MAP_SWIZZLE_128B);
  map2d(&rm.xn, xn, D_, S_, 64, 32, CU_TENSOR_MAP_SWIZZLE_128B);
  map_seg(&rm.xn1, xn, D_, 2, 1); map_seg(&rm.xn2, xn, D_, 2, 2);
  map2d(&rm.ox, ox, 4096, S_, 16, 32, CU_TENSOR_MAP_SWIZZLE_32B);
  unsigned char* xch = (unsigned char*)(((uintptr_t)sym(g_xch) + 2 * XPAGE - 1) & ~(uintptr_t)(2 * XPAGE - 1));
  cudaLaunchAttribute at[1];
  at[0].id = cudaLaunchAttributeClusterDimension;
  at[0].val.clusterDim.x = 6; at[0].val.clusterDim.y = 1; at[0].val.clusterDim.z = 1;
  cudaLaunchConfig_t cfg = {};
  cfg.attrs = at; cfg.numAttrs = 1; cfg.stream = cudaStreamPerThread;
  cfg.gridDim = dim3(96); cfg.blockDim = dim3(384); cfg.dynamicSmemBytes = R_SMEM;
  cudaLaunchKernelEx(&cfg, k_rec, rm, x, mem0, xch);
  at[0].id = cudaLaunchAttributeProgrammaticStreamSerialization;
  at[0].val.programmaticStreamSerializationAllowed = 1;
  cfg.gridDim = dim3(2 * NPAIR); cfg.dynamicSmemBytes = G_SMEM;
  cudaLaunchKernelEx(&cfg, k_gemm, gm, x, (bf16*)d_out);
}
```
